```python
import torch

def _softmax(x, axis=-1):
    return torch.softmax(x, dim=axis)
def _gelu(x):
    return torch.nn.functional.gelu(x, approximate="tanh")
def _silu(x):
    return torch.nn.functional.silu(x)
def _sigmoid(x):
    return torch.sigmoid(x)
def _layernorm(x, axis=-1, eps=1e-5):
    m = x.mean(dim=axis, keepdim=True)
    v = x.var(dim=axis, keepdim=True, unbiased=False)
    return (x - m) / torch.sqrt(v + eps)
def _scatter_add(tgt, idx, src, axis=0):
    return tgt.clone().index_add_(axis, idx, src)
def _segment_sum(src, seg, n):
    out = torch.zeros((n,) + src.shape[1:], dtype=src.dtype)
    return out.index_add_(0, seg, src)
def _pad(x, pw):
    flat = tuple(v for pair in reversed(pw) for v in pair)
    return torch.nn.functional.pad(x, flat)

kernel_name = 'recurrent_scan__ssm_conv_h3__dense_activation_mish__prompt'

def setup_inputs():

    _w = (lambda a: (lambda t: t.to(torch.bfloat16) if t.is_floating_point() else t)(torch.as_tensor(a)))
    def _A_setup():
        B, S, D = 1, 2048, 1024
        ks = 4
        return {
            "q": _w((lambda *s: torch.randn(*s, dtype=torch.bfloat16) * 0.05)(B, S, D)),
            "k": _w((lambda *s: torch.randn(*s, dtype=torch.bfloat16) * 0.8)(B, S, D)),
            "v": _w((lambda *s: torch.randn(*s, dtype=torch.bfloat16) * 0.8)(B, S, D)),
            "shift_k": _w((lambda *s: torch.randn(*s, dtype=torch.bfloat16) * 0.8)(D, ks) * 0.5),
            "ssm_k": _w((lambda *s: torch.randn(*s, dtype=torch.bfloat16) * 0.8)(D, S) * (1.0 / S ** 0.5)),
            "ssm_D": _w((lambda *s: torch.randn(*s, dtype=torch.bfloat16) * 0.8)(D)),
        }
    _A_in = _A_setup()

    def _B_setup():
        B, S, D, F = 1, 2048, 1024, 3584
        return {
            "x": _w((lambda *s: torch.randn(*s, dtype=torch.bfloat16) * 0.05)(B, S, D)),
            "w1": _w((lambda *s: torch.randn(*s, dtype=torch.bfloat16) * 0.8)(D, F) * (D ** -0.5)),
            "b1": _w((lambda *s: torch.randn(*s, dtype=torch.bfloat16) * 0.2)(F)),
            "w2": _w((lambda *s: torch.randn(*s, dtype=torch.bfloat16) * 0.2)(F, D) * (F ** -0.5)),
        }
    _B_in = _B_setup()

    return {
        "A_q": _A_in["q"],
        "A_k": _A_in["k"],
        "A_v": _A_in["v"],
        "A_shift_k": _A_in["shift_k"],
        "A_ssm_k": _A_in["ssm_k"],
        "A_ssm_D": _A_in["ssm_D"],
        "B_x": _B_in["x"],
        "B_w1": _B_in["w1"],
        "B_b1": _B_in["b1"],
        "B_w2": _B_in["w2"],
    }

def reference(A_q, A_k, A_v, A_shift_k, A_ssm_k, A_ssm_D, B_x, B_w1, B_b1, B_w2):
    def _A_ref(q, k, v, shift_k, ssm_k, ssm_D):
        B, S, D = q.shape
        ks = shift_k.shape[-1]
        k_pad = _pad(k, ((0, 0), (ks - 1, 0), (0, 0)))
        k_shift = torch.zeros_like(k)
        for t in range(ks):
            k_shift = k_shift + k_pad[:, t:t + S, :] * shift_k[:, ks - 1 - t][None, None, :]
        kv = k_shift * v
        L = 2 * S
        kv_pad = _pad(kv, ((0, 0), (0, S), (0, 0)))
        kf_pad = _pad(ssm_k, ((0, 0), (0, S)))
        kv_f = (lambda x, axes=(-2,-1): torch.fft.rfft2(x.float(), dim=axes))(kv_pad[:, None, :, :], axes=(1, 2))
        kf_f = (lambda x, axes=(-2,-1): torch.fft.rfft2(x.float(), dim=axes))(kf_pad[:, None, :], axes=(1, 2))
        kf_f = (lambda x, *d: x.permute(*d))(kf_f, 1, 2, 0)
        y_f = kv_f * kf_f[None, :, :, :]
        y = (lambda x, s, axes=(-2,-1): torch.fft.irfft2(x, s=s, dim=axes).to(torch.bfloat16))(y_f, (1, L), axes=(1, 2))[:, 0, :S, :]
        y = y + kv * ssm_D[None, None, :]
        return q * y

    def _B_ref(x, w1, b1, w2):
        h = torch.einsum("bsd,df->bsf", x, w1) + b1
        sp = torch.log1p(torch.exp(-torch.abs(h))) + torch.where(h > 0, h, torch.zeros_like(h))
        act = h * torch.tanh(sp)
        return torch.einsum("bsf,fd->bsd", act, w2)

    x = A_q
    xn = _layernorm(x, axis=-1)
    s = _A_ref(xn, A_k, A_v, A_shift_k, A_ssm_k, A_ssm_D)
    g = _silu(_B_ref(xn, B_w1, B_b1, B_w2))
    return x + s * g
```

```cpp
#include <cuda_runtime.h>
#include <cuda_bf16.h>
#include <cuda.h>
#include <stdint.h>

typedef __nv_bfloat16 bf16;
constexpr int S_ = 2048, D_ = 1024, F_ = 3584;

__device__ __align__(1024) bf16 g_act[S_ * F_];
__device__ __align__(1024) bf16 g_uT[D_ * S_];
__device__ __align__(1024) bf16 g_yT[D_ * S_];
__device__ __align__(16) float2 g_stats[S_];
__device__ __align__(16) float g_csp[16 * F_];
constexpr int FL_STATS = 0, FL_ACT0 = 16, FL_ACT1 = 32, FL_CS = 48, FL_U = 56, FL_Y = 64, FL_TICKET = 72, FL_N = 73;
__device__ __align__(128) unsigned g_flags[FL_N * 32];
#define TS(i) do {} while (0)

constexpr int SLOT1 = 49152;
constexpr int SLOT2 = 32768;
constexpr int XT_OFF = 5 * SLOT2;
constexpr int X0 = 4 * SLOT1;
constexpr int PLANE = 2048 + 448;
constexpr int CSLOT = 32 + 4096 + 2 * PLANE;
constexpr int CS_OFF = X0 + 3 * CSLOT;
constexpr int B1_OFF = CS_OFF + 1792;
constexpr int ROW_OFF = X0 + 32768;
constexpr int BAR_OFF = ROW_OFF + 1024;
constexpr int SMEM_BYTES = BAR_OFF + 256;
constexpr int B_FULL1 = BAR_OFF, B_FULL2 = BAR_OFF + 32, B_CFULL = BAR_OFF + 72, B_TABS = BAR_OFF + 96,
              B_FINX = BAR_OFF + 104, B_FINY = BAR_OFF + 112, C_CNT1 = BAR_OFF + 128, C_CNT2 = BAR_OFF + 144;

__device__ __forceinline__ uint32_t smem_u32(const void* p) { return (uint32_t)__cvta_generic_to_shared(p); }
__device__ __forceinline__ void mbar_init(uint32_t bar, int cnt) { asm volatile("mbarrier.init.shared::cta.b64 [%0], %1;" ::"r"(bar), "r"(cnt)); }
__device__ __forceinline__ void mbar_expect_tx(uint32_t bar, uint32_t bytes) { asm volatile("mbarrier.arrive.expect_tx.shared::cta.b64 _, [%0], %1;" ::"r"(bar), "r"(bytes) : "memory"); }
__device__ __forceinline__ void mbar_arrive(uint32_t bar) { asm volatile("mbarrier.arrive.shared::cta.b64 _, [%0];" ::"r"(bar) : "memory"); }
__device__ __forceinline__ bool mbar_try(uint32_t bar, uint32_t parity) {
  uint32_t ok;
  asm volatile("{\n.reg .pred P1;\nmbarrier.try_wait.parity.shared::cta.b64 P1, [%1], %2;\nselp.u32 %0, 1, 0, P1;\n}\n" : "=r"(ok) : "r"(bar), "r"(parity) : "memory");
  return ok;
}
__device__ __forceinline__ void mbar_wait(uint32_t bar, uint32_t parity) {
  for (int it = 0; it < (1 << 20); ++it) { if (mbar_try(bar, parity)) break; }
}
__device__ __forceinline__ void flag_wait(int idx, unsigned target) {
  const unsigned* p = g_flags + idx * 32;
  for (int it = 0; it < (1 << 22); ++it) {
    unsigned v;
    asm volatile("ld.acquire.gpu.global.u32 %0, [%1];" : "=r"(v) : "l"(p) : "memory");
    if (v >= target) break;
  }
}
__device__ __forceinline__ void flag_add(int idx) {
  asm volatile("red.release.gpu.global.add.u32 [%0], 1;" ::"l"(g_flags + idx * 32) : "memory");
}
__device__ __forceinline__ void fence_proxy_async() { asm volatile("fence.proxy.async;" ::: "memory"); }
__device__ __forceinline__ void fence_proxy_async_smem() { asm volatile("fence.proxy.async.shared::cta;" ::: "memory"); }
__device__ __forceinline__ void tma_2d(uint32_t dst, const CUtensorMap* m, uint32_t bar, int c0, int c1) {
  asm volatile("cp.async.bulk.tensor.2d.shared::cluster.global.mbarrier::complete_tx::bytes [%0], [%1, {%3, %4}], [%2];"
               ::"r"(dst), "l"(m), "r"(bar), "r"(c0), "r"(c1) : "memory");
}
__device__ __forceinline__ void tma_3d(uint32_t dst, const CUtensorMap* m, uint32_t bar, int c0, int c1, int c2) {
  asm volatile("cp.async.bulk.tensor.3d.shared::cluster.global.mbarrier::complete_tx::bytes [%0], [%1, {%3, %4, %5}], [%2];"
               ::"r"(dst), "l"(m), "r"(bar), "r"(c0), "r"(c1), "r"(c2) : "memory");
}
__device__ __forceinline__ void tma_store_2d(const CUtensorMap* m, uint32_t src, int c0, int c1) {
  asm volatile("cp.async.bulk.tensor.2d.global.shared::cta.bulk_group [%0, {%2, %3}], [%1];" ::"l"(m), "r"(src), "r"(c0), "r"(c1) : "memory");
}
__device__ __forceinline__ void bulk_g2s(uint32_t dst, const void* src, uint32_t bytes, uint32_t bar) {
  asm volatile("cp.async.bulk.shared::cluster.global.mbarrier::complete_tx::bytes [%0], [%1], %2, [%3];" ::"r"(dst), "l"(src), "r"(bytes), "r"(bar) : "memory");
}
__device__ __forceinline__ void bulk_s2g(void* dst, uint32_t src, uint32_t bytes) {
  asm volatile("cp.async.bulk.global.shared::cta.bulk_group [%0], [%1], %2;" ::"l"(dst), "r"(src), "r"(bytes) : "memory");
}
__device__ __forceinline__ void bulk_commit() { asm volatile("cp.async.bulk.commit_group;" ::: "memory"); }
__device__ __forceinline__ void bulk_wait_read0() { asm volatile("cp.async.bulk.wait_group.read 0;" ::: "memory"); }
__device__ __forceinline__ void bulk_wait0() { asm volatile("cp.async.bulk.wait_group 0;" ::: "memory"); }
__device__ __forceinline__ void prefetch_l2(const void* p, uint32_t bytes) {
  asm volatile("cp.async.bulk.prefetch.L2.global [%0], %1;" ::"l"(p), "r"(bytes) : "memory");
}
__device__ __forceinline__ void wg_fence() { asm volatile("wgmma.fence.sync.aligned;" ::: "memory"); }
__device__ __forceinline__ void wg_commit() { asm volatile("wgmma.commit_group.sync.aligned;" ::: "memory"); }
template <int N> __device__ __forceinline__ void wg_wait() { asm volatile("wgmma.wait_group.sync.aligned %0;" ::"n"(N) : "memory"); }
__device__ __forceinline__ void bar_sync(int id) { asm volatile("bar.sync %0, 128;" ::"r"(id) : "memory"); }
__device__ __forceinline__ uint64_t make_desc(uint32_t addr, uint32_t lbo, uint32_t sbo, uint32_t swz) {
  return (uint64_t)((addr & 0x3FFFF) >> 4) | ((uint64_t)(lbo >> 4) << 16) | ((uint64_t)(sbo >> 4) << 32) | ((uint64_t)swz << 62);
}
__device__ __forceinline__ uint32_t lds32(uint32_t a) { uint32_t v; asm volatile("ld.shared.u32 %0, [%1];" : "=r"(v) : "r"(a)); return v; }
__device__ __forceinline__ float2 lds_f2(uint32_t a) { float2 v; asm volatile("ld.shared.v2.f32 {%0,%1}, [%2];" : "=f"(v.x), "=f"(v.y) : "r"(a)); return v; }
__device__ __forceinline__ void sts32(uint32_t a, uint32_t v) { asm volatile("st.shared.u32 [%0], %1;" ::"r"(a), "r"(v) : "memory"); }
__device__ __forceinline__ void stmatrix4(uint32_t a, uint32_t r0, uint32_t r1, uint32_t r2, uint32_t r3) {
  asm volatile("stmatrix.sync.aligned.m8n8.x4.shared.b16 [%0], {%1,%2,%3,%4};" ::"r"(a), "r"(r0), "r"(r1), "r"(r2), "r"(r3) : "memory");
}
__device__ __forceinline__ void ldmatrix4(uint32_t a, uint32_t& r0, uint32_t& r1, uint32_t& r2, uint32_t& r3) {
  asm volatile("ldmatrix.sync.aligned.m8n8.x4.shared.b16 {%0,%1,%2,%3}, [%4];" : "=r"(r0), "=r"(r1), "=r"(r2), "=r"(r3) : "r"(a) : "memory");
}
__device__ __forceinline__ void ldmatrix4t(uint32_t a, uint32_t& r0, uint32_t& r1, uint32_t& r2, uint32_t& r3) {
  asm volatile("ldmatrix.sync.aligned.m8n8.x4.trans.shared.b16 {%0,%1,%2,%3}, [%4];" : "=r"(r0), "=r"(r1), "=r"(r2), "=r"(r3) : "r"(a) : "memory");
}
__device__ __forceinline__ uint32_t pack_bf16(float lo, float hi) {
  uint32_t r; asm("cvt.rn.bf16x2.f32 %0, %1, %2;" : "=r"(r) : "f"(hi), "f"(lo)); return r;
}
__device__ __forceinline__ float bf_lo(uint32_t v) { return __uint_as_float(v << 16); }
__device__ __forceinline__ float bf_hi(uint32_t v) { return __uint_as_float(v & 0xffff0000u); }
__device__ __forceinline__ float round_bf(float x) { return __bfloat162float(__float2bfloat16_rn(x)); }
__device__ __forceinline__ float ex2f(float x) { float r; asm("ex2.approx.ftz.f32 %0, %1;" : "=f"(r) : "f"(x)); return r; }
__device__ __forceinline__ float rcpf(float x) { float r; asm("rcp.approx.ftz.f32 %0, %1;" : "=f"(r) : "f"(x)); return r; }
__device__ __forceinline__ float mishf(float h) {
  float e = ex2f(h * 1.4426950408889634f);
  float d = fmaf(e, e + 2.f, 2.f);
  return h * fmaf(-2.f, rcpf(d), 1.f);
}
__device__ __forceinline__ uint32_t hmul2(uint32_t a, uint32_t b) { uint32_t r; asm("mul.rn.bf16x2 %0, %1, %2;" : "=r"(r) : "r"(a), "r"(b)); return r; }
__device__ __forceinline__ uint32_t hadd2(uint32_t a, uint32_t b) { uint32_t r; asm("add.rn.bf16x2 %0, %1, %2;" : "=r"(r) : "r"(a), "r"(b)); return r; }

__device__ __forceinline__ void wgmma_ss256(float (&d)[128], uint64_t da, uint64_t db, int scale_d) {
  asm volatile("{\n.reg .pred p;\nsetp.ne.b32 p, %130, 0;\n"
   "wgmma.mma_async.sync.aligned.m64n256k16.f32.bf16.bf16 {%0, %1, %2, %3, %4, %5, %6, %7, %8, %9, %10, %11, %12, %13, %14, %15, %16, %17, %18, %19, %20, %21, %22, %23, %24, %25, %26, %27, %28, %29, %30, %31, %32, %33, %34, %35, %36, %37, %38, %39, %40, %41, %42, %43, %44, %45, %46, %47, %48, %49, %50, %51, %52, %53, %54, %55, %56, %57, %58, %59, %60, %61, %62, %63, %64, %65, %66, %67, %68, %69, %70, %71, %72, %73, %74, %75, %76, %77, %78, %79, %80, %81, %82, %83, %84, %85, %86, %87, %88, %89, %90, %91, %92, %93, %94, %95, %96, %97, %98, %99, %100, %101, %102, %103, %104, %105, %106, %107, %108, %109, %110, %111, %112, %113, %114, %115, %116, %117, %118, %119, %120, %121, %122, %123, %124, %125, %126, %127}, %128, %129, p, 1, 1, 0, 1;\n}\n"
   : "+f"(d[0]), "+f"(d[1]), "+f"(d[2]), "+f"(d[3]), "+f"(d[4]), "+f"(d[5]), "+f"(d[6]), "+f"(d[7]), "+f"(d[8]), "+f"(d[9]), "+f"(d[10]), "+f"(d[11]), "+f"(d[12]), "+f"(d[13]), "+f"(d[14]), "+f"(d[15]), "+f"(d[16]), "+f"(d[17]), "+f"(d[18]), "+f"(d[19]), "+f"(d[20]), "+f"(d[21]), "+f"(d[22]), "+f"(d[23]), "+f"(d[24]), "+f"(d[25]), "+f"(d[26]), "+f"(d[27]), "+f"(d[28]), "+f"(d[29]), "+f"(d[30]), "+f"(d[31]), "+f"(d[32]), "+f"(d[33]), "+f"(d[34]), "+f"(d[35]), "+f"(d[36]), "+f"(d[37]), "+f"(d[38]), "+f"(d[39]), "+f"(d[40]), "+f"(d[41]), "+f"(d[42]), "+f"(d[43]), "+f"(d[44]), "+f"(d[45]), "+f"(d[46]), "+f"(d[47]), "+f"(d[48]), "+f"(d[49]), "+f"(d[50]), "+f"(d[51]), "+f"(d[52]), "+f"(d[53]), "+f"(d[54]), "+f"(d[55]), "+f"(d[56]), "+f"(d[57]), "+f"(d[58]), "+f"(d[59]), "+f"(d[60]), "+f"(d[61]), "+f"(d[62]), "+f"(d[63]), "+f"(d[64]), "+f"(d[65]), "+f"(d[66]), "+f"(d[67]), "+f"(d[68]), "+f"(d[69]), "+f"(d[70]), "+f"(d[71]), "+f"(d[72]), "+f"(d[73]), "+f"(d[74]), "+f"(d[75]), "+f"(d[76]), "+f"(d[77]), "+f"(d[78]), "+f"(d[79]), "+f"(d[80]), "+f"(d[81]), "+f"(d[82]), "+f"(d[83]), "+f"(d[84]), "+f"(d[85]), "+f"(d[86]), "+f"(d[87]), "+f"(d[88]), "+f"(d[89]), "+f"(d[90]), "+f"(d[91]), "+f"(d[92]), "+f"(d[93]), "+f"(d[94]), "+f"(d[95]), "+f"(d[96]), "+f"(d[97]), "+f"(d[98]), "+f"(d[99]), "+f"(d[100]), "+f"(d[101]), "+f"(d[102]), "+f"(d[103]), "+f"(d[104]), "+f"(d[105]), "+f"(d[106]), "+f"(d[107]), "+f"(d[108]), "+f"(d[109]), "+f"(d[110]), "+f"(d[111]), "+f"(d[112]), "+f"(d[113]), "+f"(d[114]), "+f"(d[115]), "+f"(d[116]), "+f"(d[117]), "+f"(d[118]), "+f"(d[119]), "+f"(d[120]), "+f"(d[121]), "+f"(d[122]), "+f"(d[123]), "+f"(d[124]), "+f"(d[125]), "+f"(d[126]), "+f"(d[127])
   : "l"(da), "l"(db), "r"(scale_d));
}
__device__ __forceinline__ void wgmma_ss192(float (&d)[96], uint64_t da, uint64_t db, int scale_d) {
  asm volatile("{\n.reg .pred p;\nsetp.ne.b32 p, %98, 0;\n"
   "wgmma.mma_async.sync.aligned.m64n192k16.f32.bf16.bf16 {%0, %1, %2, %3, %4, %5, %6, %7, %8, %9, %10, %11, %12, %13, %14, %15, %16, %17, %18, %19, %20, %21, %22, %23, %24, %25, %26, %27, %28, %29, %30, %31, %32, %33, %34, %35, %36, %37, %38, %39, %40, %41, %42, %43, %44, %45, %46, %47, %48, %49, %50, %51, %52, %53, %54, %55, %56, %57, %58, %59, %60, %61, %62, %63, %64, %65, %66, %67, %68, %69, %70, %71, %72, %73, %74, %75, %76, %77, %78, %79, %80, %81, %82, %83, %84, %85, %86, %87, %88, %89, %90, %91, %92, %93, %94, %95}, %96, %97, p, 1, 1, 0, 1;\n}\n"
   : "+f"(d[0]), "+f"(d[1]), "+f"(d[2]), "+f"(d[3]), "+f"(d[4]), "+f"(d[5]), "+f"(d[6]), "+f"(d[7]), "+f"(d[8]), "+f"(d[9]), "+f"(d[10]), "+f"(d[11]), "+f"(d[12]), "+f"(d[13]), "+f"(d[14]), "+f"(d[15]), "+f"(d[16]), "+f"(d[17]), "+f"(d[18]), "+f"(d[19]), "+f"(d[20]), "+f"(d[21]), "+f"(d[22]), "+f"(d[23]), "+f"(d[24]), "+f"(d[25]), "+f"(d[26]), "+f"(d[27]), "+f"(d[28]), "+f"(d[29]), "+f"(d[30]), "+f"(d[31]), "+f"(d[32]), "+f"(d[33]), "+f"(d[34]), "+f"(d[35]), "+f"(d[36]), "+f"(d[37]), "+f"(d[38]), "+f"(d[39]), "+f"(d[40]), "+f"(d[41]), "+f"(d[42]), "+f"(d[43]), "+f"(d[44]), "+f"(d[45]), "+f"(d[46]), "+f"(d[47]), "+f"(d[48]), "+f"(d[49]), "+f"(d[50]), "+f"(d[51]), "+f"(d[52]), "+f"(d[53]), "+f"(d[54]), "+f"(d[55]), "+f"(d[56]), "+f"(d[57]), "+f"(d[58]), "+f"(d[59]), "+f"(d[60]), "+f"(d[61]), "+f"(d[62]), "+f"(d[63]), "+f"(d[64]), "+f"(d[65]), "+f"(d[66]), "+f"(d[67]), "+f"(d[68]), "+f"(d[69]), "+f"(d[70]), "+f"(d[71]), "+f"(d[72]), "+f"(d[73]), "+f"(d[74]), "+f"(d[75]), "+f"(d[76]), "+f"(d[77]), "+f"(d[78]), "+f"(d[79]), "+f"(d[80]), "+f"(d[81]), "+f"(d[82]), "+f"(d[83]), "+f"(d[84]), "+f"(d[85]), "+f"(d[86]), "+f"(d[87]), "+f"(d[88]), "+f"(d[89]), "+f"(d[90]), "+f"(d[91]), "+f"(d[92]), "+f"(d[93]), "+f"(d[94]), "+f"(d[95])
   : "l"(da), "l"(db), "r"(scale_d));
}
__device__ __forceinline__ void wgmma_ss128(float (&d)[64], uint64_t da, uint64_t db, int scale_d) {
  asm volatile("{\n.reg .pred p;\nsetp.ne.b32 p, %66, 0;\n"
   "wgmma.mma_async.sync.aligned.m64n128k16.f32.bf16.bf16 {%0, %1, %2, %3, %4, %5, %6, %7, %8, %9, %10, %11, %12, %13, %14, %15, %16, %17, %18, %19, %20, %21, %22, %23, %24, %25, %26, %27, %28, %29, %30, %31, %32, %33, %34, %35, %36, %37, %38, %39, %40, %41, %42, %43, %44, %45, %46, %47, %48, %49, %50, %51, %52, %53, %54, %55, %56, %57, %58, %59, %60, %61, %62, %63}, %64, %65, p, 1, 1, 0, 1;\n}\n"
   : "+f"(d[0]), "+f"(d[1]), "+f"(d[2]), "+f"(d[3]), "+f"(d[4]), "+f"(d[5]), "+f"(d[6]), "+f"(d[7]), "+f"(d[8]), "+f"(d[9]), "+f"(d[10]), "+f"(d[11]), "+f"(d[12]), "+f"(d[13]), "+f"(d[14]), "+f"(d[15]), "+f"(d[16]), "+f"(d[17]), "+f"(d[18]), "+f"(d[19]), "+f"(d[20]), "+f"(d[21]), "+f"(d[22]), "+f"(d[23]), "+f"(d[24]), "+f"(d[25]), "+f"(d[26]), "+f"(d[27]), "+f"(d[28]), "+f"(d[29]), "+f"(d[30]), "+f"(d[31]), "+f"(d[32]), "+f"(d[33]), "+f"(d[34]), "+f"(d[35]), "+f"(d[36]), "+f"(d[37]), "+f"(d[38]), "+f"(d[39]), "+f"(d[40]), "+f"(d[41]), "+f"(d[42]), "+f"(d[43]), "+f"(d[44]), "+f"(d[45]), "+f"(d[46]), "+f"(d[47]), "+f"(d[48]), "+f"(d[49]), "+f"(d[50]), "+f"(d[51]), "+f"(d[52]), "+f"(d[53]), "+f"(d[54]), "+f"(d[55]), "+f"(d[56]), "+f"(d[57]), "+f"(d[58]), "+f"(d[59]), "+f"(d[60]), "+f"(d[61]), "+f"(d[62]), "+f"(d[63])
   : "l"(da), "l"(db), "r"(scale_d));
}

template <int OFF> __device__ __forceinline__ void wgmma_rs32(float (&d)[64], const uint32_t (&a)[4], uint64_t db, int scale_d) {
  asm volatile("{\n.reg .pred p;\nsetp.ne.b32 p, %21, 0;\n"
               "wgmma.mma_async.sync.aligned.m64n32k16.f32.bf16.bf16 {%0,%1,%2,%3,%4,%5,%6,%7,%8,%9,%10,%11,%12,%13,%14,%15}, {%16,%17,%18,%19}, %20, p, 1, 1, 0;\n}\n"
               : "+f"(d[OFF + 0]), "+f"(d[OFF + 1]), "+f"(d[OFF + 2]), "+f"(d[OFF + 3]), "+f"(d[OFF + 4]), "+f"(d[OFF + 5]), "+f"(d[OFF + 6]), "+f"(d[OFF + 7]),
                 "+f"(d[OFF + 8]), "+f"(d[OFF + 9]), "+f"(d[OFF + 10]), "+f"(d[OFF + 11]), "+f"(d[OFF + 12]), "+f"(d[OFF + 13]), "+f"(d[OFF + 14]), "+f"(d[OFF + 15])
               : "r"(a[0]), "r"(a[1]), "r"(a[2]), "r"(a[3]), "l"(db), "r"(scale_d));
}

struct Params {
  CUtensorMap tmX, tmW1a, tmW1b, tmActL, tmActS, tmW2, tmYT, tmOut;
  const bf16 *x, *k, *v, *shift_k, *ssm_k, *ssm_D, *w1, *b1, *w2;
};

__device__ __forceinline__ void conv_load_a(uint32_t (&a)[4], uint32_t haddr, int d) {
  uint32_t w0 = lds32(haddr + d * 128), w1 = lds32(haddr + d * 128 + 4), w2 = lds32(haddr + d * 128 + 8);
  a[0] = __byte_perm(w0, w1, 0x5432); a[1] = w1; a[2] = __byte_perm(w1, w2, 0x5432); a[3] = w2;
}
template <int i> __device__ __forceinline__ void conv_rec(float (&acc)[64], uint32_t (&cur)[4][4], uint32_t (&nxt)[4][4], uint32_t haddr, uint64_t db0) {
  wg_fence();
  wgmma_rs32<0>(acc, cur[0], db0 + i * 4, i != 0);
  wgmma_rs32<16>(acc, cur[0], db0 + i * 4 + 32, i != 0);
  wgmma_rs32<32>(acc, cur[0], db0 + i * 4 + 64, i != 0);
  wgmma_rs32<0>(acc, cur[1], db0 + i * 4 + 96, 1);
  wgmma_rs32<48>(acc, cur[0], db0 + i * 4 + 96, i != 0);
  wgmma_rs32<16>(acc, cur[2], db0 + i * 4 + 64, 1);
  wgmma_rs32<0>(acc, cur[2], db0 + i * 4 + 32, 1);
  wgmma_rs32<32>(acc, cur[2], db0 + i * 4 + 96, 1);
  wgmma_rs32<16>(acc, cur[3], db0 + i * 4 + 96, 1);
  wgmma_rs32<0>(acc, cur[3], db0 + i * 4 + 64, 1);
  wg_commit();
  if constexpr (i + 1 < 8) {
    wg_wait<1>();
    conv_load_a(nxt[0], haddr, i + 1); conv_load_a(nxt[1], haddr, 24 + i + 1); conv_load_a(nxt[2], haddr, 8 + i + 1); conv_load_a(nxt[3], haddr, 16 + i + 1);
    conv_rec<i + 1>(acc, nxt, cur, haddr, db0);
  }
}
__device__ __forceinline__ uint32_t conv_out(float y0, float y1, uint32_t uw, uint32_t dv2) {
  uint32_t ud = hmul2(__byte_perm(uw, uw, 0x1032), dv2);
  return hadd2(pack_bf16(y0, y1), ud);
}
template <class FN> __device__ __forceinline__ void conv_channel(uint32_t sl, uint32_t dv2, bf16* ydst, int t128, FN mid) {
  const int lane = t128 & 31, w = t128 >> 5, g = lane >> 2, t = lane & 3;
  const uint32_t haddr = sl + ((g & 1) + 2 * w + 8 * (g >> 1) + 2 * t) * 4;
  const uint32_t ub = sl + 32 + 4096;
  const uint64_t db0 = make_desc(ub, PLANE, 128, 0);
  float acc[64];
  {
    uint32_t A0[4][4], A1[4][4];
    conv_load_a(A0[0], haddr, 0); conv_load_a(A0[1], haddr, 24); conv_load_a(A0[2], haddr, 8); conv_load_a(A0[3], haddr, 16);
    conv_rec<0>(acc, A0, A1, haddr, db0);
    wg_wait<0>();
  }
  mid();
  const int q = g >> 1; const bool hi = q & 1;
  const int src1 = hi ? (((lane ^ 8) & ~3) | ((t + 3) & 3)) : (lane ^ 8);
  float z[2][16];
#pragma unroll
  for (int i = 0; i < 2; i++) {
    float prev = 0.f;
#pragma unroll
    for (int k = 0; k < 16; k++) {
      float r = __shfl_sync(0xffffffff, acc[4 * k + 2 * i + 1], src1);
      float add = (hi && t == 0) ? prev : r;
      prev = r;
      z[i][k] = acc[4 * k + 2 * i] + add;
    }
  }
  const int a = g >> 2;
  const int src2 = a ? (((lane ^ 16) & ~3) | ((t + 3) & 3)) : (((lane ^ 16) & ~3) | ((t + 1) & 3));
  float y[2][8];
#pragma unroll
  for (int i = 0; i < 2; i++) {
#pragma unroll
    for (int k = 0; k < 8; k++) {
      float snd = a ? (t == 0 ? z[i][k + 1] : z[i][k]) : (t == 3 ? z[i][7 + k] : z[i][8 + k]);
      float r = __shfl_sync(0xffffffff, snd, src2);
      y[i][k] = (a ? z[i][8 + k] : z[i][k]) + r;
    }
  }
  const float e0 = __shfl_sync(0xffffffff, acc[61], lane ^ 24), e1 = __shfl_sync(0xffffffff, acc[63], lane ^ 24);
  bar_sync(3);
  const int off = 2 * (g & 1) + 4 * w;
  const int kap = 14 - off;
  const uint32_t uoff = ub + ((kap >> 1) & 1) * PLANE + (kap >> 2) * 4;
  const uint32_t yoff = sl + 32 + (127 * 16 + off) * 2;
  const int Bp0 = (a ? 62 : 0) + 2 * t - (int)hi;
#pragma unroll
  for (int k = 0; k < 8; k++) {
    int Bp = Bp0 + 8 * k;
    if (k > 0 || Bp >= 0) sts32(yoff - Bp * 32, conv_out(y[0][k], y[1][k], lds32(uoff + Bp * 16), dv2));
  }
  if (t == 3 && q < 2) {
    int Bp = 126 - q;
    sts32(yoff - Bp * 32, conv_out(z[0][15] + (q ? e0 : 0.f), z[1][15] + (q ? e1 : 0.f), lds32(uoff + Bp * 16), dv2));
    if (q == 0) sts32(yoff - 127 * 32, conv_out(acc[61], acc[63], lds32(uoff + 127 * 16), dv2));
  }
  fence_proxy_async_smem();
  bar_sync(3);
  if (t128 == 0) { bulk_s2g(ydst, sl + 32, 4096); bulk_commit(); }
}

__global__ void __launch_bounds__(384, 1) h3_ffn_kernel(const __grid_constant__ Params P) {
  extern __shared__ __align__(1024) uint8_t smem_raw[];
  const uint32_t sb = smem_u32(smem_raw);
  const int tid = threadIdx.x;
  const int warp = __shfl_sync(0xffffffff, tid >> 5, 0), wg = warp >> 2;
  const int lane = tid & 31, t128 = tid & 127, w = warp & 3;
  const int rb = blockIdx.x >> 3, j = blockIdx.x & 7;

  auto load_g1 = [&](int n) {
    const uint32_t st = sb + (n & 3) * SLOT1, bar = sb + B_FULL1 + (n & 3) * 8;
    if (n < 16) {
      mbar_expect_tx(bar, 49152);
      tma_2d(st, &P.tmX, bar, n * 64, rb * 128);
      tma_3d(st + 16384, &P.tmW1a, bar, 0, n * 64, j * 4);
    } else {
      mbar_expect_tx(bar, 40960);
      tma_2d(st, &P.tmX, bar, (n - 16) * 64, rb * 128);
      tma_3d(st + 16384, &P.tmW1b, bar, 0, (n - 16) * 64, 32 + j * 3);
    }
  };
  auto load_g2 = [&](int n, int s) {
    const uint32_t st = sb + s * SLOT2, bar = sb + B_FULL2 + s * 8;
    mbar_expect_tx(bar, 32768);
    tma_2d(st, &P.tmActL, bar, n * 64, rb * 128);
    tma_3d(st + 16384, &P.tmW2, bar, 0, n * 64, j * 2);
  };

  if (tid == 0) {
    for (int s = 0; s < 4; s++) mbar_init(sb + B_FULL1 + s * 8, 1);
    for (int s = 0; s < 5; s++) mbar_init(sb + B_FULL2 + s * 8, 1);
    for (int s = 0; s < 3; s++) mbar_init(sb + B_CFULL + s * 8, 1);
    mbar_init(sb + B_TABS, 128);
    mbar_init(sb + B_FINX, 1);
    mbar_init(sb + B_FINY, 1);
    for (int s = 0; s < 9; s++) sts32(sb + C_CNT1 + s * 4, 0);
    asm volatile("fence.mbarrier_init.release.cluster;" ::: "memory");
    fence_proxy_async_smem();
    for (int n = 0; n < 4; n++) load_g1(n);
  }
  __syncthreads();

  if (wg < 2) {
    asm volatile("setmaxnreg.inc.sync.aligned.u32 184;");
    const int g = lane >> 2, t = lane & 3;
    auto last_arriver = [&](uint32_t cnt) -> bool {
      uint32_t old;
      asm volatile("atom.shared.add.u32 %0, [%1], 1;" : "=r"(old) : "r"(cnt) : "memory");
      return old & 1;
    };
    auto release1 = [&](int n) {
      if (t128 == 0) {
        if (last_arriver(sb + C_CNT1 + (n & 3) * 4)) {
          if (n < 28) load_g1(n + 4);
          else if (n == 28) { flag_wait(FL_ACT0 + rb, 16); fence_proxy_async(); load_g2(0, 0); }
          else if (n == 29) { flag_wait(FL_ACT0 + rb, 16); fence_proxy_async(); load_g2(1, 1); load_g2(2, 2); }
          else if (n == 30) { flag_wait(FL_ACT0 + rb, 16); fence_proxy_async(); load_g2(3, 3); }
          else { flag_wait(FL_ACT0 + rb, 16); fence_proxy_async(); load_g2(4, 4); }
        }
      }
    };
    const uint64_t descA0 = make_desc(sb + wg * 8192, 16, 1024, 1);
    const uint64_t descB0 = make_desc(sb + 16384, 8192, 1024, 1);
    const int row0 = wg * 64 + w * 16 + g;
    const int mrow = w * 16 + (lane & 7) + ((lane >> 3) & 1) * 8;
    const uint32_t moff = mrow * 128;
    const uint32_t mx = (lane >> 4) ^ (lane & 7);
    uint32_t hp[48];
    float r0, r1, m0, m1;

    {
      float acc[128];
#pragma unroll 1
      for (int kt = 0; kt < 16; kt++) {
        const int s = kt & 3;
        mbar_wait(sb + B_FULL1 + s * 8, (kt >> 2) & 1);
        if (kt == 0 && tid == 0) TS(0);
        wg_fence();
#pragma unroll
        for (int k = 0; k < 4; k++) wgmma_ss256(acc, descA0 + s * (SLOT1 >> 4) + k * 2, descB0 + s * (SLOT1 >> 4) + k * 128, (kt | k) != 0);
        wg_commit();
        if (kt > 0) { wg_wait<1>(); release1(kt - 1); }
      }
      mbar_wait(sb + B_TABS, 0);
      mbar_wait(sb + B_FULL1 + wg * 8, 0);
      { float2 a = lds_f2(sb + ROW_OFF + row0 * 8), b = lds_f2(sb + ROW_OFF + (row0 + 8) * 8); m0 = -a.x; r0 = a.y; m1 = -b.x; r1 = b.y; }
      wg_wait<0>();
      release1(15);
      if (tid == 0) TS(1);
#pragma unroll
      for (int q = 15; q >= 0; q--) {
        float2 c0 = lds_f2(sb + CS_OFF + (16 * q + 2 * t) * 4), c1 = lds_f2(sb + CS_OFF + (16 * q + 8 + 2 * t) * 4);
        uint32_t p0 = pack_bf16(fmaf(m0, c0.x, acc[8 * q]), fmaf(m0, c0.y, acc[8 * q + 1]));
        uint32_t p1 = pack_bf16(fmaf(m1, c0.x, acc[8 * q + 2]), fmaf(m1, c0.y, acc[8 * q + 3]));
        uint32_t p2 = pack_bf16(fmaf(m0, c1.x, acc[8 * q + 4]), fmaf(m0, c1.y, acc[8 * q + 5]));
        uint32_t p3 = pack_bf16(fmaf(m1, c1.x, acc[8 * q + 6]), fmaf(m1, c1.y, acc[8 * q + 7]));
        if (q >= 12) stmatrix4(sb + wg * SLOT1 + 40960 + moff + ((mx ^ (2 * (q & 3))) << 4), p0, p1, p2, p3);
        else { hp[4 * q] = p0; hp[4 * q + 1] = p1; hp[4 * q + 2] = p2; hp[4 * q + 3] = p3; }
      }
    }
    auto mish_group = [&](int q, uint32_t btab, uint32_t buf) {
      const uint32_t addr = buf + moff + ((mx ^ (2 * (q & 3))) << 4);
      uint32_t p0, p1, p2, p3;
      if (q >= 12) ldmatrix4(addr, p0, p1, p2, p3);
      else { p0 = hp[4 * q]; p1 = hp[4 * q + 1]; p2 = hp[4 * q + 2]; p3 = hp[4 * q + 3]; }
      float2 b0 = lds_f2(btab + (16 * q + 2 * t) * 4), b1 = lds_f2(btab + (16 * q + 8 + 2 * t) * 4);
      uint32_t o0 = pack_bf16(mishf(fmaf(r0, bf_lo(p0), b0.x)), mishf(fmaf(r0, bf_hi(p0), b0.y)));
      uint32_t o1 = pack_bf16(mishf(fmaf(r1, bf_lo(p1), b0.x)), mishf(fmaf(r1, bf_hi(p1), b0.y)));
      uint32_t o2 = pack_bf16(mishf(fmaf(r0, bf_lo(p2), b1.x)), mishf(fmaf(r0, bf_hi(p2), b1.y)));
      uint32_t o3 = pack_bf16(mishf(fmaf(r1, bf_lo(p3), b1.x)), mishf(fmaf(r1, bf_hi(p3), b1.y)));
      stmatrix4(addr, o0, o1, o2, o3);
    };
    auto store_chunk = [&](uint32_t buf, int col) {
      fence_proxy_async_smem();
      if (t128 == 0) bulk_wait_read0();
      bar_sync(1 + wg);
      if (t128 == 0) { tma_store_2d(&P.tmActS, buf, col, rb * 128 + wg * 64); bulk_commit(); }
    };
    auto publish = [&](int fl) {
      if (t128 == 0) { bulk_wait0(); fence_proxy_async(); flag_add(fl); }
    };
    {
      float acc[96];
#pragma unroll
      for (int kt = 0; kt < 16; kt++) {
        const int s = kt & 3;
        mbar_wait(sb + B_FULL1 + s * 8, (kt >> 2) & 1);
        wg_fence();
#pragma unroll
        for (int k = 0; k < 4; k++) wgmma_ss192(acc, descA0 + s * (SLOT1 >> 4) + k * 2, descB0 + s * (SLOT1 >> 4) + k * 128, (kt | k) != 0);
        wg_commit();
        if (kt > 0) { wg_wait<1>(); release1(16 + kt - 1); }
        if (kt >= 1 && kt <= 8) {
          const int o = (kt - 1) >> 1, c = (o + 3) & 3;
          const uint32_t buf = sb + ((o & 1) * 2 + wg) * SLOT1 + 40960;
          mish_group(4 * c + 2 * ((kt - 1) & 1), sb + B1_OFF, buf);
          mish_group(4 * c + 2 * ((kt - 1) & 1) + 1, sb + B1_OFF, buf);
          if (!(kt & 1)) store_chunk(buf, j * 256 + c * 64);
        }
        if (kt == 10) publish(FL_ACT0 + rb);
      }
      wg_wait<0>();
      release1(31);
      if (tid == 0) TS(2);
#pragma unroll
      for (int k = 0; k < 24; k++) {
        float2 c = lds_f2(sb + CS_OFF + (256 + 8 * k + 2 * t) * 4);
        hp[2 * k] = pack_bf16(fmaf(m0, c.x, acc[4 * k]), fmaf(m0, c.y, acc[4 * k + 1]));
        hp[2 * k + 1] = pack_bf16(fmaf(m1, c.x, acc[4 * k + 2]), fmaf(m1, c.y, acc[4 * k + 3]));
      }
    }
    {
      float acc[64];
      auto release2 = [&](int n, int s) {
        if (t128 == 0) {
          if (last_arriver(sb + C_CNT2 + s * 4)) {
            if (n + 5 < 56) {
              if (n + 5 >= 32 && n + 5 < 34) { flag_wait(FL_ACT1 + rb, 16); fence_proxy_async(); }
              load_g2(n + 5, s);
            }
            if (n == 24) {
              mbar_expect_tx(sb + B_FINX, 32768);
              tma_2d(sb + XT_OFF, &P.tmX, sb + B_FINX, j * 128, rb * 128);
              tma_2d(sb + XT_OFF + 16384, &P.tmX, sb + B_FINX, j * 128 + 64, rb * 128);
            }
          }
        }
      };
      auto step2 = [&](int kt, int s, uint32_t ph) {
        mbar_wait(sb + B_FULL2 + s * 8, ph);
        wg_fence();
#pragma unroll
        for (int k = 0; k < 4; k++) wgmma_ss128(acc, descA0 + s * (SLOT2 >> 4) + k * 2, descB0 + s * (SLOT2 >> 4) + k * 128, (kt | k) != 0);
        wg_commit();
        if (kt > 0) { wg_wait<1>(); release2(kt - 1, s == 0 ? 4 : s - 1); }
      };
#pragma unroll
      for (int kt = 0; kt < 20; kt++) {
        step2(kt, kt % 5, (kt / 5) & 1);
        if (kt >= 5 && kt <= 16) {
          const int q = kt - 5, c = q >> 2;
          const uint32_t buf = sb + XT_OFF + wg * 16384 + (c & 1) * 8192;
          mish_group(q, sb + B1_OFF + 1024, buf);
          if ((q & 3) == 3) store_chunk(buf, 2048 + j * 192 + c * 64);
        }
        if (kt == 19) publish(FL_ACT1 + rb);
      }
      {
        int s = 0; uint32_t ph = 0;
#pragma unroll 1
        for (int kt = 20; kt < 56; kt++) {
          step2(kt, s, ph);
          if (++s == 5) { s = 0; ph ^= 1; }
        }
      }
      if (tid == 0) TS(3);
      mbar_wait(sb + B_FINX, 0);
      mbar_wait(sb + B_FINY, 0);
      if (tid == 0) TS(4);
      uint32_t xf[32], sf[32];
      const uint32_t yrow = (lane & 7) + (lane >> 4) * 8;
      const uint32_t ychunk = 2 * w + ((lane >> 3) & 1);
      const uint32_t ybase = sb + X0 + wg * 16384 + yrow * 128 + ((ychunk ^ (lane & 7)) << 4);
#pragma unroll
      for (int q = 0; q < 8; q++) {
        const uint32_t xa = sb + XT_OFF + (q >> 2) * 16384 + wg * 8192 + moff + ((mx ^ (2 * (q & 3))) << 4);
        ldmatrix4(xa, xf[4 * q], xf[4 * q + 1], xf[4 * q + 2], xf[4 * q + 3]);
        ldmatrix4t(ybase + q * 2048, sf[4 * q], sf[4 * q + 1], sf[4 * q + 2], sf[4 * q + 3]);
      }
#pragma unroll
      for (int i = 0; i < 32; i++) {
        const float mm = (i & 1) ? m1 : m0, rr = (i & 1) ? r1 : r0;
        uint32_t dd = pack_bf16(bf_lo(xf[i]) + mm, bf_hi(xf[i]) + mm);
        uint32_t xn = pack_bf16(bf_lo(dd) * rr, bf_hi(dd) * rr);
        sf[i] = hmul2(xn, sf[i]);
      }
      wg_wait<0>();
      if (tid == 0) TS(5);
#pragma unroll
      for (int q = 0; q < 8; q++) {
        uint32_t o[4];
#pragma unroll
        for (int i = 0; i < 4; i++) {
          float z0 = acc[8 * q + 2 * i], z1 = acc[8 * q + 2 * i + 1];
          float g0 = z0 * rcpf(1.f + ex2f(-1.4426950408889634f * z0));
          float g1 = z1 * rcpf(1.f + ex2f(-1.4426950408889634f * z1));
          o[i] = pack_bf16(fmaf(bf_lo(sf[4 * q + i]), g0, bf_lo(xf[4 * q + i])), fmaf(bf_hi(sf[4 * q + i]), g1, bf_hi(xf[4 * q + i])));
        }
        const uint32_t xa = sb + XT_OFF + (q >> 2) * 16384 + wg * 8192 + moff + ((mx ^ (2 * (q & 3))) << 4);
        stmatrix4(xa, o[0], o[1], o[2], o[3]);
      }
      fence_proxy_async_smem();
      bar_sync(1 + wg);
      if (t128 == 0) {
        tma_store_2d(&P.tmOut, sb + XT_OFF + wg * 8192, j * 128, rb * 128 + wg * 64);
        tma_store_2d(&P.tmOut, sb + XT_OFF + 16384 + wg * 8192, j * 128 + 64, rb * 128 + wg * 64);
        bulk_commit();
        if (tid == 0) {
          unsigned old = atomicAdd(&g_flags[FL_TICKET * 32], 1u);
          if (old == gridDim.x - 1) { for (int i = 0; i < FL_N; i++) g_flags[i * 32] = 0; }
        }
        bulk_wait_read0();
        if (tid == 0) TS(6);
      }
    }
  } else {
    asm volatile("setmaxnreg.dec.sync.aligned.u32 128;");
    for (int i = t128; i < 3 * (8 + 224); i += 128) {
      const int sl = i / 232, r = i % 232;
      const uint32_t a = r < 8 ? r * 4 : (r < 120 ? 32 + 4096 + 2048 + (r - 8) * 4 : 32 + 4096 + PLANE + 2048 + (r - 120) * 4);
      sts32(sb + X0 + sl * CSLOT + a, 0);
    }
    {
      uint4 xv[4][4];
      const int row = rb * 128 + j * 16 + w * 4;
#pragma unroll
      for (int r = 0; r < 4; r++)
#pragma unroll
        for (int c = 0; c < 4; c++) xv[r][c] = __ldg((const uint4*)(P.x + (size_t)(row + r) * D_) + c * 32 + lane);
#pragma unroll
      for (int r = 0; r < 4; r++) {
        float s = 0.f;
#pragma unroll
        for (int c = 0; c < 4; c++) {
          const uint32_t* u = (const uint32_t*)&xv[r][c];
#pragma unroll
          for (int e = 0; e < 4; e++) s += bf_lo(u[e]) + bf_hi(u[e]);
        }
#pragma unroll
        for (int o = 16; o; o >>= 1) s += __shfl_xor_sync(0xffffffff, s, o);
        const float mean = s * (1.f / D_);
        float v = 0.f;
#pragma unroll
        for (int c = 0; c < 4; c++) {
          const uint32_t* u = (const uint32_t*)&xv[r][c];
#pragma unroll
          for (int e = 0; e < 4; e++) { float a = bf_lo(u[e]) - mean, b = bf_hi(u[e]) - mean; v = fmaf(a, a, v); v = fmaf(b, b, v); }
        }
#pragma unroll
        for (int o = 16; o; o >>= 1) v += __shfl_xor_sync(0xffffffff, v, o);
        const float sd = round_bf(sqrtf(round_bf(round_bf(v * (1.f / D_)) + 1e-5f)));
        if (lane == 0) g_stats[row + r] = make_float2(round_bf(mean), 1.f / sd);
      }
    }
    {
      const uint32_t scr = sb + X0 + 32;
#pragma unroll
      for (int part = 0; part < 2; part++) {
        const int col = part ? 2048 + j * 192 + lane * 8 : j * 256 + lane * 8;
        float cs[8];
#pragma unroll
        for (int e = 0; e < 8; e++) cs[e] = 0.f;
        if (part == 0 || lane < 24) {
          uint4 wv[16];
#pragma unroll
          for (int r = 0; r < 16; r++) wv[r] = __ldg((const uint4*)(P.w1 + (size_t)(rb * 64 + w * 16 + r) * F_ + col));
#pragma unroll
          for (int r = 0; r < 16; r++) {
            const uint32_t* u = (const uint32_t*)&wv[r];
#pragma unroll
            for (int e = 0; e < 4; e++) { cs[2 * e] += bf_lo(u[e]); cs[2 * e + 1] += bf_hi(u[e]); }
          }
          const uint32_t a = scr + part * CSLOT + w * 1024 + lane * 32;
          asm volatile("st.shared.v4.f32 [%0], {%1,%2,%3,%4};" ::"r"(a), "f"(cs[0]), "f"(cs[1]), "f"(cs[2]), "f"(cs[3]) : "memory");
          asm volatile("st.shared.v4.f32 [%0], {%1,%2,%3,%4};" ::"r"(a + 16), "f"(cs[4]), "f"(cs[5]), "f"(cs[6]), "f"(cs[7]) : "memory");
        }
      }
      bar_sync(3);
#pragma unroll
      for (int i = 0; i < 4; i++) {
        const int c = t128 + i * 128;
        if (c < 448) {
          const uint32_t a = scr + (c >= 256 ? CSLOT + (c - 256) * 4 : c * 4);
          const float v = __uint_as_float(lds32(a)) + __uint_as_float(lds32(a + 1024)) + __uint_as_float(lds32(a + 2048)) + __uint_as_float(lds32(a + 3072));
          g_csp[rb * F_ + j * 448 + c] = v;
        }
      }
      bar_sync(3);
      if (t128 == 0) { __threadfence(); flag_add(FL_STATS + rb); flag_add(FL_CS + j); TS(8); }
    }
    {
      const int ch = j * 128 + lane * 4;
      uint32_t wt[4][2];
      {
        const uint4 a = __ldg((const uint4*)(P.shift_k + ch * 4)), b = __ldg((const uint4*)(P.shift_k + ch * 4 + 8));
        wt[0][0] = __byte_perm(a.x, a.z, 0x5410); wt[1][0] = __byte_perm(a.x, a.z, 0x7632);
        wt[2][0] = __byte_perm(a.y, a.w, 0x5410); wt[3][0] = __byte_perm(a.y, a.w, 0x7632);
        wt[0][1] = __byte_perm(b.x, b.z, 0x5410); wt[1][1] = __byte_perm(b.x, b.z, 0x7632);
        wt[2][1] = __byte_perm(b.y, b.w, 0x5410); wt[3][1] = __byte_perm(b.y, b.w, 0x7632);
      }
#pragma unroll 1
      for (int blk = 0; blk < 2; blk++) {
        const int r0_ = rb * 128 + w * 32 + blk * 16;
        uint2 kk[19], vv[16];
#pragma unroll
        for (int r = 0; r < 19; r++) {
          const int row = r0_ - 3 + r;
          kk[r] = (r >= 3 || row >= 0) ? __ldg((const uint2*)(P.k + (size_t)row * D_ + ch)) : make_uint2(0u, 0u);
        }
#pragma unroll
        for (int r = 0; r < 16; r++) vv[r] = __ldg((const uint2*)(P.v + (size_t)(r0_ + r) * D_ + ch));
#pragma unroll
        for (int r = 0; r < 16; r++) {
          uint32_t a = hadd2(hadd2(hadd2(hmul2(kk[r].x, wt[3][0]), hmul2(kk[r + 1].x, wt[2][0])), hmul2(kk[r + 2].x, wt[1][0])), hmul2(kk[r + 3].x, wt[0][0]));
          uint32_t b = hadd2(hadd2(hadd2(hmul2(kk[r].y, wt[3][1]), hmul2(kk[r + 1].y, wt[2][1])), hmul2(kk[r + 2].y, wt[1][1])), hmul2(kk[r + 3].y, wt[0][1]));
          vv[r].x = hmul2(a, vv[r].x); vv[r].y = hmul2(b, vv[r].y);
        }
        const int rho = 127 - (r0_ >> 4);
#pragma unroll
        for (int p = 0; p < 2; p++) {
          uint4 o0, o1, o2, o3;
#define UW(t_) vv[15 - 4 * (t_) - 2 * p], vv[14 - 4 * (t_) - 2 * p]
          auto lo_x = [](uint2 a, uint2 b) { return __byte_perm(a.x, b.x, 0x5410); };
          auto hi_x = [](uint2 a, uint2 b) { return __byte_perm(a.x, b.x, 0x7632); };
          auto lo_y = [](uint2 a, uint2 b) { return __byte_perm(a.y, b.y, 0x5410); };
          auto hi_y = [](uint2 a, uint2 b) { return __byte_perm(a.y, b.y, 0x7632); };
          o0 = make_uint4(lo_x(UW(0)), lo_x(UW(1)), lo_x(UW(2)), lo_x(UW(3)));
          o1 = make_uint4(hi_x(UW(0)), hi_x(UW(1)), hi_x(UW(2)), hi_x(UW(3)));
          o2 = make_uint4(lo_y(UW(0)), lo_y(UW(1)), lo_y(UW(2)), lo_y(UW(3)));
          o3 = make_uint4(hi_y(UW(0)), hi_y(UW(1)), hi_y(UW(2)), hi_y(UW(3)));
#undef UW
          uint4* dst = (uint4*)(g_uT + (size_t)ch * S_ + p * 1024 + rho * 8);
          dst[0] = o0; dst[256] = o1; dst[512] = o2; dst[768] = o3;
        }
      }
      bar_sync(3);
      if (t128 == 0) { __threadfence(); flag_add(FL_U + j); TS(9); }
    }
    if (t128 == 32) {
      for (int i = 0; i < 4; i++) prefetch_l2((const uint8_t*)P.w2 + (size_t)blockIdx.x * 57344 + i * 14336, 14336);
    }
    if (t128 == 0) { flag_wait(FL_STATS + rb, 8); flag_wait(FL_CS + j, 16); }
    bar_sync(3);
    {
      const float2 st = __ldcg(&g_stats[rb * 128 + t128]);
      asm volatile("st.shared.v2.f32 [%0], {%1,%2};" ::"r"(sb + ROW_OFF + t128 * 8), "f"(st.x), "f"(st.y) : "memory");
      if (t128 < 112) {
        float4 a = make_float4(0.f, 0.f, 0.f, 0.f);
#pragma unroll
        for (int r = 0; r < 16; r++) {
          const float4 v = __ldcg((const float4*)(g_csp + r * F_ + j * 448) + t128);
          a.x += v.x; a.y += v.y; a.z += v.z; a.w += v.w;
        }
        asm volatile("st.shared.v4.f32 [%0], {%1,%2,%3,%4};" ::"r"(sb + CS_OFF + t128 * 16), "f"(a.x), "f"(a.y), "f"(a.z), "f"(a.w) : "memory");
        const int col = t128 < 64 ? j * 256 + t128 * 4 : 2048 + j * 192 + (t128 - 64) * 4;
        const uint2 b = __ldg((const uint2*)(P.b1 + col));
        asm volatile("st.shared.v4.f32 [%0], {%1,%2,%3,%4};" ::"r"(sb + B1_OFF + t128 * 16), "f"(bf_lo(b.x)), "f"(bf_hi(b.x)), "f"(bf_lo(b.y)), "f"(bf_hi(b.y)) : "memory");
      }
      mbar_arrive(sb + B_TABS);
      if (t128 == 0) TS(10);
    }
    const int ch0 = j * 128 + rb * 8;
    auto cload = [&](int c) {
      const uint32_t sl = sb + X0 + (c % 3) * CSLOT, bar = sb + B_CFULL + (c % 3) * 8;
      mbar_expect_tx(bar, 8192);
      bulk_g2s(sl + 32, P.ssm_k + (size_t)(ch0 + c) * S_, 4096, bar);
      bulk_g2s(sl + 32 + 4096, g_uT + (size_t)(ch0 + c) * S_, 2048, bar);
      bulk_g2s(sl + 32 + 4096 + PLANE, g_uT + (size_t)(ch0 + c) * S_ + 1024, 2048, bar);
    };
    fence_proxy_async_smem();
    bar_sync(3);
    if (t128 == 0) { flag_wait(FL_U + j, 16); fence_proxy_async(); cload(0); cload(1); TS(11); }
    const uint32_t dall = (uint32_t)__bfloat16_as_ushort(P.ssm_D[ch0 + (lane & 7)]) * 0x10001u;
#pragma unroll 1
    for (int c = 0; c < 8; c++) {
      mbar_wait(sb + B_CFULL + (c % 3) * 8, (c / 3) & 1);
      const uint32_t dv2 = __shfl_sync(0xffffffff, dall, c);
      conv_channel(sb + X0 + (c % 3) * CSLOT, dv2, g_yT + (size_t)(ch0 + c) * S_, t128, [&]() {
        if (t128 == 0 && c > 0) {
          bulk_wait0(); fence_proxy_async(); flag_add(FL_Y + j);
        }
        if (t128 == 0 && c + 2 < 8) cload(c + 2);
      });
      if (t128 == 0) TS(12 + c);
    }
    if (t128 == 0) {
      bulk_wait0(); fence_proxy_async(); flag_add(FL_Y + j);
      mbar_wait(sb + B_FINX, 0);
      flag_wait(FL_Y + j, 128);
      fence_proxy_async();
      mbar_expect_tx(sb + B_FINY, 32768);
      tma_2d(sb + X0, &P.tmYT, sb + B_FINY, rb * 128, j * 128);
      tma_2d(sb + X0 + 16384, &P.tmYT, sb + B_FINY, rb * 128 + 64, j * 128);
      TS(20);
    }
  }
}

typedef CUresult (*EncFn)(CUtensorMap*, CUtensorMapDataType, cuuint32_t, void*, const cuuint64_t*, const cuuint64_t*, const cuuint32_t*,
                          const cuuint32_t*, CUtensorMapInterleave, CUtensorMapSwizzle, CUtensorMapL2promotion, CUtensorMapFloatOOBfill);
static void make_map(EncFn enc, CUtensorMap* m, const void* ptr, int rank, const cuuint64_t* dims, const cuuint64_t* strides, const cuuint32_t* box) {
  cuuint32_t es[3] = {1, 1, 1};
  enc(m, CU_TENSOR_MAP_DATA_TYPE_BFLOAT16, rank, (void*)ptr, dims, strides, box, es, CU_TENSOR_MAP_INTERLEAVE_NONE,
      CU_TENSOR_MAP_SWIZZLE_128B, CU_TENSOR_MAP_L2_PROMOTION_L2_256B, CU_TENSOR_MAP_FLOAT_OOB_FILL_NONE);
}
static void map2d(EncFn enc, CUtensorMap* m, const void* p, uint64_t cols, uint64_t rows, uint32_t bc, uint32_t br) {
  cuuint64_t d[2] = {cols, rows}, s[1] = {cols * 2}; cuuint32_t b[2] = {bc, br};
  make_map(enc, m, p, 2, d, s, b);
}
static void map3d(EncFn enc, CUtensorMap* m, const void* p, uint64_t cols, uint64_t rows, uint32_t nchunk) {
  cuuint64_t d[3] = {64, rows, cols / 64}, s[2] = {cols * 2, 128}; cuuint32_t b[3] = {64, 64, nchunk};
  make_map(enc, m, p, 3, d, s, b);
}

extern "C" void kernel_launch(void* const* d_in, const int* in_sizes, int n_in, void* d_out, int out_size) {
  (void)in_sizes; (void)n_in; (void)out_size;
  void* fp = nullptr; cudaDriverEntryPointQueryResult qr;
  cudaGetDriverEntryPoint("cuTensorMapEncodeTiled", &fp, cudaEnableDefault, &qr);
  EncFn enc = (EncFn)fp;
  void *act, *yT;
  cudaGetSymbolAddress(&act, g_act);
  cudaGetSymbolAddress(&yT, g_yT);
  Params P;
  P.x = (const bf16*)d_in[0]; P.k = (const bf16*)d_in[1]; P.v = (const bf16*)d_in[2]; P.shift_k = (const bf16*)d_in[3];
  P.ssm_k = (const bf16*)d_in[4]; P.ssm_D = (const bf16*)d_in[5]; P.w1 = (const bf16*)d_in[7]; P.b1 = (const bf16*)d_in[8]; P.w2 = (const bf16*)d_in[9];
  map2d(enc, &P.tmX, P.x, D_, S_, 64, 128);
  map3d(enc, &P.tmW1a, P.w1, F_, D_, 4);
  map3d(enc, &P.tmW1b, P.w1, F_, D_, 3);
  map2d(enc, &P.tmActL, act, F_, S_, 64, 128);
  map2d(enc, &P.tmActS, act, F_, S_, 64, 64);
  map3d(enc, &P.tmW2, P.w2, D_, F_, 2);
  map2d(enc, &P.tmYT, yT, S_, D_, 64, 128);
  map2d(enc, &P.tmOut, d_out, D_, S_, 64, 64);
  cudaFuncSetAttribute(h3_ffn_kernel, cudaFuncAttributeMaxDynamicSharedMemorySize, SMEM_BYTES);
  h3_ffn_kernel<<<128, 384, SMEM_BYTES, cudaStreamPerThread>>>(P);
}
```

```cpp
#include <cuda_runtime.h>
#include <cuda_bf16.h>
#include <cuda.h>
#include <stdint.h>

typedef __nv_bfloat16 bf16;
#define NCONV 8
#define CVI 2
#define NSIT 16
constexpr int SPIN_M = 1 << 20, SPIN_F = 1 << 22;
constexpr int S_ = 2048, D_ = 1024, F_ = 3584;

__device__ __align__(1024) bf16 g_act[S_ * F_];
__device__ __align__(1024) bf16 g_uT[D_ * S_];
__device__ __align__(1024) bf16 g_yT[D_ * S_];
constexpr int FL_ACT = 0, FL_STATS = 7, FL_CS = 16 * 32, FL_U = FL_CS + 2, FL_Y = FL_CS + 3, FL_TICKET = 24 * 32, FL_LINES = 25;
constexpr int CSUM = FL_LINES * 32, RSUM = CSUM + F_, FL_WORDS = RSUM + 2 * S_;
__device__ __align__(128) unsigned g_flags[FL_WORDS];
#define TS(i) do {} while (0)
#define CT(i) do {} while (0)
#define CSEL 0

constexpr int SLOT0 = 49152;
constexpr int SLOT1 = 40960;
constexpr int SLOT2 = 32768;
constexpr int XT_OFF = 5 * SLOT2;
constexpr int X0 = 4 * SLOT0;
constexpr int CH = 2048 + 128, CU1 = CH + 4096, CSLOT = CU1 + 2048 + 128;
constexpr int EX_OFF = X0 + 2 * CSLOT;
constexpr int TAB_OFF = EX_OFF + 12288;
constexpr int ROW_OFF = TAB_OFF + 4608;
constexpr int KB_OFF = X0 + 16384;
constexpr int BAR_OFF = ROW_OFF + 1024;
constexpr int SMEM_BYTES = BAR_OFF + 384 + 128;
constexpr int B_FULL1 = BAR_OFF, B_FULL2 = B_FULL1 + 32, B_CFULL = B_FULL2 + 40, B_CRDY = B_CFULL + 16, B_FINX = B_CRDY + 16, B_FINY = B_FINX + 8,
              B_TABS = B_FINY + 8, B_DONE = B_TABS + 8, B_AFREE = B_DONE + 8,
              B_EMPTY1 = B_AFREE + 16, B_EMPTY2 = B_EMPTY1 + 32;
constexpr int B_YRDY = B_EMPTY2 + 40, B_S2 = B_YRDY + 16,
              B_S1 = B_S2 + 8, B_ARDY = B_S1 + 8,
              B_S3 = B_ARDY + 16, B_TAB1 = B_S3 + 8, B_S4 = B_TAB1 + 8;

__device__ __forceinline__ uint32_t smem_u32(const void* p) { return (uint32_t)__cvta_generic_to_shared(p); }
__device__ __forceinline__ void mbar_init(uint32_t bar, int cnt) { asm volatile("mbarrier.init.shared::cta.b64 [%0], %1;" ::"r"(bar), "r"(cnt)); }
__device__ __forceinline__ void mbar_expect_tx(uint32_t bar, uint32_t bytes) { asm volatile("mbarrier.arrive.expect_tx.shared::cta.b64 _, [%0], %1;" ::"r"(bar), "r"(bytes) : "memory"); }
__device__ __forceinline__ void mbar_arrive(uint32_t bar) { asm volatile("mbarrier.arrive.shared::cta.b64 _, [%0];" ::"r"(bar) : "memory"); }
__device__ __forceinline__ void arrive_if(uint32_t bar, int z) {
  asm volatile("{\n.reg .pred p;\nsetp.eq.u32 p, %1, 0;\n@p mbarrier.arrive.shared::cta.b64 _, [%0];\n}\n" ::"r"(bar), "r"(z) : "memory");
}
__device__ __forceinline__ void arrive_cl(uint32_t bar, int z) {
  asm volatile("{\n.reg .pred p;\nsetp.eq.u32 p, %1, 0;\n@p mbarrier.arrive.shared::cluster.b64 _, [%0];\n}\n" ::"r"(bar), "r"(z) : "memory");
}
__device__ __forceinline__ bool mbar_try(uint32_t bar, uint32_t parity) {
  uint32_t ok;
  asm volatile("{\n.reg .pred P1;\nmbarrier.try_wait.parity.shared::cta.b64 P1, [%1], %2;\nselp.u32 %0, 1, 0, P1;\n}\n" : "=r"(ok) : "r"(bar), "r"(parity) : "memory");
  return ok;
}
__device__ __forceinline__ void mbar_wait(uint32_t bar, uint32_t parity) {
#pragma unroll 1
  for (int it = 0; it < SPIN_M; ++it) { if (mbar_try(bar, parity)) break; }
}
__device__ __forceinline__ unsigned flag_ld(const unsigned* f) {
  unsigned v;
  asm volatile("ld.relaxed.gpu.global.u32 %0, [%1];" : "=r"(v) : "l"(f) : "memory");
  return v;
}
__device__ __forceinline__ void flag_wait(const unsigned* idx, unsigned target) {
#pragma unroll 1
  for (int it = 0; it < SPIN_F; ++it) { if (flag_ld(idx) >= target) break; }
}
__device__ __forceinline__ bool elect_one() {
  uint32_t p;
  asm volatile("{\n.reg .pred P;\nelect.sync _|P, 0xffffffff;\nselp.u32 %0, 1, 0, P;\n}\n" : "=r"(p));
  return p;
}
__device__ __forceinline__ int uni(int v) {
#define UNI 1
  return __shfl_sync(0xffffffff, v, 0);
}
__device__ __forceinline__ void fence_gpu() { asm volatile("fence.acq_rel.gpu;" ::: "memory"); }
__device__ __forceinline__ void flag_add(unsigned* f, unsigned n = 1) {
  asm volatile("red.relaxed.gpu.global.add.u32 [%0], %1;" ::"l"(f), "r"(n) : "memory");
}
__device__ __forceinline__ void fence_proxy_async() { asm volatile("fence.proxy.async;" ::: "memory"); }
__device__ __forceinline__ void fence_proxy_async_smem() { asm volatile("fence.proxy.async.shared::cta;" ::: "memory"); }
__device__ __forceinline__ void fence_init() { asm volatile("fence.mbarrier_init.release.cluster;\nfence.proxy.async.shared::cta;" ::: "memory"); }
__device__ __forceinline__ void tma_2d(uint32_t dst, const CUtensorMap* m, uint32_t bar, int c0, int c1) {
  asm volatile("cp.async.bulk.tensor.2d.shared::cluster.global.mbarrier::complete_tx::bytes [%0], [%1, {%3, %4}], [%2];"
               ::"r"(dst), "l"(m), "r"(bar), "r"(c0), "r"(c1) : "memory");
}
__device__ __forceinline__ void tma_3d(uint32_t dst, const CUtensorMap* m, uint32_t bar, int c0, int c1, int c2) {
  asm volatile("cp.async.bulk.tensor.3d.shared::cluster.global.mbarrier::complete_tx::bytes [%0], [%1, {%3, %4, %5}], [%2];"
               ::"r"(dst), "l"(m), "r"(bar), "r"(c0), "r"(c1), "r"(c2) : "memory");
}
__device__ __forceinline__ void tma_3d_mc(uint32_t dst, const CUtensorMap* m, uint32_t bar, int c1, int c2) {
  asm volatile("cp.async.bulk.tensor.3d.shared::cluster.global.mbarrier::complete_tx::bytes.multicast::cluster [%0], [%1, {%3, %4, %5}], [%2], %6;"
               ::"r"(dst), "l"(m), "r"(bar), "r"(0), "r"(c1), "r"(c2), "h"((uint16_t)3) : "memory");
}
__device__ __forceinline__ void tma_store_2d(const CUtensorMap* m, uint32_t src, int c0, int c1) {
  asm volatile("cp.async.bulk.tensor.2d.global.shared::cta.bulk_group [%0, {%2, %3}], [%1];" ::"l"(m), "r"(src), "r"(c0), "r"(c1) : "memory");
}
__device__ __forceinline__ void bulk_g2s(uint32_t dst, const void* src, uint32_t bytes, uint32_t bar) {
  asm volatile("cp.async.bulk.shared::cluster.global.mbarrier::complete_tx::bytes [%0], [%1], %2, [%3];" ::"r"(dst), "l"(src), "r"(bytes), "r"(bar) : "memory");
}
__device__ __forceinline__ void bulk_s2g(void* dst, uint32_t src, uint32_t bytes) {
  asm volatile("cp.async.bulk.global.shared::cta.bulk_group [%0], [%1], %2;" ::"l"(dst), "r"(src), "r"(bytes) : "memory");
}
__device__ __forceinline__ void bulk_commit() { asm volatile("cp.async.bulk.commit_group;" ::: "memory"); }
__device__ __forceinline__ void bulk_wait_read0() { asm volatile("cp.async.bulk.wait_group.read 0;" ::: "memory"); }
__device__ __forceinline__ void bulk_wait0() { asm volatile("cp.async.bulk.wait_group 0;" ::: "memory"); }
__device__ __forceinline__ void prefetch_l2(const void* p, uint32_t bytes) {
  asm volatile("cp.async.bulk.prefetch.L2.global [%0], %1;" ::"l"(p), "r"(bytes) : "memory");
}
__device__ __forceinline__ void wg_fence() { asm volatile("wgmma.fence.sync.aligned;" ::: "memory"); }
__device__ __forceinline__ void wg_commit() { asm volatile("wgmma.commit_group.sync.aligned;" ::: "memory"); }
template <int N> __device__ __forceinline__ void wg_wait() { asm volatile("wgmma.wait_group.sync.aligned %0;" ::"n"(N) : "memory"); }
__device__ __forceinline__ void cta_sync() { asm volatile("barrier.cluster.wait.aligned;" ::: "memory"); }
__device__ __forceinline__ void bar_sync(int id) { asm volatile("bar.sync %0, 128;" ::"r"(id) : "memory"); }
__device__ __forceinline__ uint64_t make_desc(uint32_t addr, uint32_t lbo, uint32_t sbo, uint32_t swz) {
  return (uint64_t)((addr & 0x3FFFF) >> 4) | ((uint64_t)(lbo >> 4) << 16) | ((uint64_t)(sbo >> 4) << 32) | ((uint64_t)swz << 62);
}
__device__ __forceinline__ uint32_t lds32(uint32_t a) { uint32_t v; asm volatile("ld.shared.u32 %0, [%1];" : "=r"(v) : "r"(a)); return v; }
__device__ __forceinline__ uint4 lds128(uint32_t a) { uint4 v; asm volatile("ld.shared.v4.u32 {%0,%1,%2,%3}, [%4];" : "=r"(v.x), "=r"(v.y), "=r"(v.z), "=r"(v.w) : "r"(a) : "memory"); return v; }
__device__ __forceinline__ uint4 ldg128(const uint4* p) { uint4 v; asm volatile("ld.global.nc.L1::no_allocate.v4.u32 {%0,%1,%2,%3}, [%4];" : "=r"(v.x), "=r"(v.y), "=r"(v.z), "=r"(v.w) : "l"(p)); return v; }
__device__ __forceinline__ uint2 ldg64p(const uint2* p) { uint2 v; asm volatile("ld.global.nc.L1::no_allocate.L2::256B.v2.u32 {%0,%1}, [%2];" : "=r"(v.x), "=r"(v.y) : "l"(p)); return v; }
__device__ __forceinline__ uint2 ldg64n(const void* p) { uint2 v; asm volatile("ld.global.nc.L1::no_allocate.v2.u32 {%0,%1}, [%2];" : "=r"(v.x), "=r"(v.y) : "l"(p)); return v; }
__device__ __forceinline__ float ldg_bf(const bf16* p) { uint32_t v; asm volatile("ld.global.nc.u16 %0, [%1];" : "=r"(v) : "l"(p)); return __uint_as_float(v); }
__device__ __forceinline__ uint2 lds64(uint32_t a) { uint2 v; asm volatile("ld.shared.v2.u32 {%0,%1}, [%2];" : "=r"(v.x), "=r"(v.y) : "r"(a) : "memory"); return v; }
__device__ __forceinline__ void sts128(uint32_t a, uint32_t x, uint32_t y, uint32_t z, uint32_t w) { asm volatile("st.shared.v4.u32 [%0], {%1,%2,%3,%4};" ::"r"(a), "r"(x), "r"(y), "r"(z), "r"(w) : "memory"); }
__device__ __forceinline__ float2 lds_f2(uint32_t a) { float2 v; asm volatile("ld.shared.v2.f32 {%0,%1}, [%2];" : "=f"(v.x), "=f"(v.y) : "r"(a)); return v; }
__device__ __forceinline__ void sts32(uint32_t a, uint32_t v) { asm volatile("st.shared.u32 [%0], %1;" ::"r"(a), "r"(v) : "memory"); }
__device__ __forceinline__ void sts128f(uint32_t a, float4 v) { asm volatile("st.shared.v4.f32 [%0], {%1,%2,%3,%4};" ::"r"(a), "f"(v.x), "f"(v.y), "f"(v.z), "f"(v.w) : "memory"); }
__device__ __forceinline__ void stmatrix4(uint32_t a, uint32_t r0, uint32_t r1, uint32_t r2, uint32_t r3) {
  asm volatile("stmatrix.sync.aligned.m8n8.x4.shared.b16 [%0], {%1,%2,%3,%4};" ::"r"(a), "r"(r0), "r"(r1), "r"(r2), "r"(r3) : "memory");
}
__device__ __forceinline__ void stmatrix2(uint32_t a, uint32_t r0, uint32_t r1) {
  asm volatile("stmatrix.sync.aligned.m8n8.x2.shared.b16 [%0], {%1,%2};" ::"r"(a), "r"(r0), "r"(r1) : "memory");
}
__device__ __forceinline__ void ldmatrix2(uint32_t a, uint32_t& r0, uint32_t& r1) {
  asm volatile("ldmatrix.sync.aligned.m8n8.x2.shared.b16 {%0,%1}, [%2];" : "=r"(r0), "=r"(r1) : "r"(a) : "memory");
}
__device__ __forceinline__ void ldmatrix4(uint32_t a, uint32_t& r0, uint32_t& r1, uint32_t& r2, uint32_t& r3) {
  asm volatile("ldmatrix.sync.aligned.m8n8.x4.shared.b16 {%0,%1,%2,%3}, [%4];" : "=r"(r0), "=r"(r1), "=r"(r2), "=r"(r3) : "r"(a) : "memory");
}
__device__ __forceinline__ void ldmatrix4t(uint32_t a, uint32_t& r0, uint32_t& r1, uint32_t& r2, uint32_t& r3) {
  asm volatile("ldmatrix.sync.aligned.m8n8.x4.trans.shared.b16 {%0,%1,%2,%3}, [%4];" : "=r"(r0), "=r"(r1), "=r"(r2), "=r"(r3) : "r"(a) : "memory");
}
__device__ __forceinline__ uint32_t pack_bf16(float lo, float hi) {
  uint32_t r; asm("cvt.rn.bf16x2.f32 %0, %1, %2;" : "=r"(r) : "f"(hi), "f"(lo)); return r;
}
__device__ __forceinline__ float bf_lo(uint32_t v) { return __uint_as_float(v << 16); }
__device__ __forceinline__ float bf_hi(uint32_t v) { return __uint_as_float(v & 0xffff0000u); }
__device__ __forceinline__ float round_bf(float x) { return __bfloat162float(__float2bfloat16_rn(x)); }
__device__ __forceinline__ float ex2f(float x) { float r; asm("ex2.approx.ftz.f32 %0, %1;" : "=f"(r) : "f"(x)); return r; }
__device__ __forceinline__ float rcpf(float x) { float r; asm("rcp.approx.ftz.f32 %0, %1;" : "=f"(r) : "f"(x)); return r; }
__device__ __forceinline__ float tanhf_(float x) { float r; asm("tanh.approx.f32 %0, %1;" : "=f"(r) : "f"(x)); return r; }
__device__ __forceinline__ float mish2(float h2) {
  float e = ex2f(h2);
  float d = fmaf(e, e + 2.f, 2.f);
  return h2 * fmaf(-2.f * 0.6931471805599453f, rcpf(d), 0.6931471805599453f);
}
__device__ __forceinline__ uint32_t hfma2(uint32_t a, uint32_t b, uint32_t c) { uint32_t r; asm("fma.rn.bf16x2 %0, %1, %2, %3;" : "=r"(r) : "r"(a), "r"(b), "r"(c)); return r; }
__device__ __forceinline__ uint32_t hmul2(uint32_t a, uint32_t b) { uint32_t r; asm("mul.rn.bf16x2 %0, %1, %2;" : "=r"(r) : "r"(a), "r"(b)); return r; }
__device__ __forceinline__ uint32_t hadd2(uint32_t a, uint32_t b) { uint32_t r; asm("add.rn.bf16x2 %0, %1, %2;" : "=r"(r) : "r"(a), "r"(b)); return r; }

__device__ __forceinline__ void wgmma_ss192(float (&d)[96], uint64_t da, uint64_t db, int scale_d) {
  asm volatile("{\n.reg .pred p;\nsetp.ne.b32 p, %98, 0;\n"
   "wgmma.mma_async.sync.aligned.m64n192k16.f32.bf16.bf16 {%0, %1, %2, %3, %4, %5, %6, %7, %8, %9, %10, %11, %12, %13, %14, %15, %16, %17, %18, %19, %20, %21, %22, %23, %24, %25, %26, %27, %28, %29, %30, %31, %32, %33, %34, %35, %36, %37, %38, %39, %40, %41, %42, %43, %44, %45, %46, %47, %48, %49, %50, %51, %52, %53, %54, %55, %56, %57, %58, %59, %60, %61, %62, %63, %64, %65, %66, %67, %68, %69, %70, %71, %72, %73, %74, %75, %76, %77, %78, %79, %80, %81, %82, %83, %84, %85, %86, %87, %88, %89, %90, %91, %92, %93, %94, %95}, %96, %97, p, 1, 1, 0, 1;\n}\n"
   : "+f"(d[0]), "+f"(d[1]), "+f"(d[2]), "+f"(d[3]), "+f"(d[4]), "+f"(d[5]), "+f"(d[6]), "+f"(d[7]), "+f"(d[8]), "+f"(d[9]), "+f"(d[10]), "+f"(d[11]), "+f"(d[12]), "+f"(d[13]), "+f"(d[14]), "+f"(d[15]), "+f"(d[16]), "+f"(d[17]), "+f"(d[18]), "+f"(d[19]), "+f"(d[20]), "+f"(d[21]), "+f"(d[22]), "+f"(d[23]), "+f"(d[24]), "+f"(d[25]), "+f"(d[26]), "+f"(d[27]), "+f"(d[28]), "+f"(d[29]), "+f"(d[30]), "+f"(d[31]), "+f"(d[32]), "+f"(d[33]), "+f"(d[34]), "+f"(d[35]), "+f"(d[36]), "+f"(d[37]), "+f"(d[38]), "+f"(d[39]), "+f"(d[40]), "+f"(d[41]), "+f"(d[42]), "+f"(d[43]), "+f"(d[44]), "+f"(d[45]), "+f"(d[46]), "+f"(d[47]), "+f"(d[48]), "+f"(d[49]), "+f"(d[50]), "+f"(d[51]), "+f"(d[52]), "+f"(d[53]), "+f"(d[54]), "+f"(d[55]), "+f"(d[56]), "+f"(d[57]), "+f"(d[58]), "+f"(d[59]), "+f"(d[60]), "+f"(d[61]), "+f"(d[62]), "+f"(d[63]), "+f"(d[64]), "+f"(d[65]), "+f"(d[66]), "+f"(d[67]), "+f"(d[68]), "+f"(d[69]), "+f"(d[70]), "+f"(d[71]), "+f"(d[72]), "+f"(d[73]), "+f"(d[74]), "+f"(d[75]), "+f"(d[76]), "+f"(d[77]), "+f"(d[78]), "+f"(d[79]), "+f"(d[80]), "+f"(d[81]), "+f"(d[82]), "+f"(d[83]), "+f"(d[84]), "+f"(d[85]), "+f"(d[86]), "+f"(d[87]), "+f"(d[88]), "+f"(d[89]), "+f"(d[90]), "+f"(d[91]), "+f"(d[92]), "+f"(d[93]), "+f"(d[94]), "+f"(d[95])
   : "l"(da), "l"(db), "r"(scale_d));
}
__device__ __forceinline__ void wgmma_ss128(float (&d)[64], uint64_t da, uint64_t db, int scale_d) {
  asm volatile("{\n.reg .pred p;\nsetp.ne.b32 p, %66, 0;\n"
   "wgmma.mma_async.sync.aligned.m64n128k16.f32.bf16.bf16 {%0, %1, %2, %3, %4, %5, %6, %7, %8, %9, %10, %11, %12, %13, %14, %15, %16, %17, %18, %19, %20, %21, %22, %23, %24, %25, %26, %27, %28, %29, %30, %31, %32, %33, %34, %35, %36, %37, %38, %39, %40, %41, %42, %43, %44, %45, %46, %47, %48, %49, %50, %51, %52, %53, %54, %55, %56, %57, %58, %59, %60, %61, %62, %63}, %64, %65, p, 1, 1, 0, 1;\n}\n"
   : "+f"(d[0]), "+f"(d[1]), "+f"(d[2]), "+f"(d[3]), "+f"(d[4]), "+f"(d[5]), "+f"(d[6]), "+f"(d[7]), "+f"(d[8]), "+f"(d[9]), "+f"(d[10]), "+f"(d[11]), "+f"(d[12]), "+f"(d[13]), "+f"(d[14]), "+f"(d[15]), "+f"(d[16]), "+f"(d[17]), "+f"(d[18]), "+f"(d[19]), "+f"(d[20]), "+f"(d[21]), "+f"(d[22]), "+f"(d[23]), "+f"(d[24]), "+f"(d[25]), "+f"(d[26]), "+f"(d[27]), "+f"(d[28]), "+f"(d[29]), "+f"(d[30]), "+f"(d[31]), "+f"(d[32]), "+f"(d[33]), "+f"(d[34]), "+f"(d[35]), "+f"(d[36]), "+f"(d[37]), "+f"(d[38]), "+f"(d[39]), "+f"(d[40]), "+f"(d[41]), "+f"(d[42]), "+f"(d[43]), "+f"(d[44]), "+f"(d[45]), "+f"(d[46]), "+f"(d[47]), "+f"(d[48]), "+f"(d[49]), "+f"(d[50]), "+f"(d[51]), "+f"(d[52]), "+f"(d[53]), "+f"(d[54]), "+f"(d[55]), "+f"(d[56]), "+f"(d[57]), "+f"(d[58]), "+f"(d[59]), "+f"(d[60]), "+f"(d[61]), "+f"(d[62]), "+f"(d[63])
   : "l"(da), "l"(db), "r"(scale_d));
}
template <int N> __device__ __forceinline__ void wgmma_rs(float (&d)[64], const uint32_t (&a)[4], uint64_t db, int scale_d);
template <> __device__ __forceinline__ void wgmma_rs<8>(float (&d)[64], const uint32_t (&a)[4], uint64_t db, int scale_d) {
  asm volatile("{\n.reg .pred p;\nsetp.ne.b32 p, %9, 0;\n"
   "wgmma.mma_async.sync.aligned.m64n8k16.f32.bf16.bf16 {%0, %1, %2, %3}, {%4,%5,%6,%7}, %8, p, 1, 1, 0;\n}\n"
   : "+f"(d[0]), "+f"(d[1]), "+f"(d[2]), "+f"(d[3])
   : "r"(a[0]), "r"(a[1]), "r"(a[2]), "r"(a[3]), "l"(db), "r"(scale_d));
}
template <> __device__ __forceinline__ void wgmma_rs<16>(float (&d)[64], const uint32_t (&a)[4], uint64_t db, int scale_d) {
  asm volatile("{\n.reg .pred p;\nsetp.ne.b32 p, %13, 0;\n"
   "wgmma.mma_async.sync.aligned.m64n16k16.f32.bf16.bf16 {%0, %1, %2, %3, %4, %5, %6, %7}, {%8,%9,%10,%11}, %12, p, 1, 1, 0;\n}\n"
   : "+f"(d[0]), "+f"(d[1]), "+f"(d[2]), "+f"(d[3]), "+f"(d[4]), "+f"(d[5]), "+f"(d[6]), "+f"(d[7])
   : "r"(a[0]), "r"(a[1]), "r"(a[2]), "r"(a[3]), "l"(db), "r"(scale_d));
}
template <> __device__ __forceinline__ void wgmma_rs<24>(float (&d)[64], const uint32_t (&a)[4], uint64_t db, int scale_d) {
  asm volatile("{\n.reg .pred p;\nsetp.ne.b32 p, %17, 0;\n"
   "wgmma.mma_async.sync.aligned.m64n24k16.f32.bf16.bf16 {%0, %1, %2, %3, %4, %5, %6, %7, %8, %9, %10, %11}, {%12,%13,%14,%15}, %16, p, 1, 1, 0;\n}\n"
   : "+f"(d[0]), "+f"(d[1]), "+f"(d[2]), "+f"(d[3]), "+f"(d[4]), "+f"(d[5]), "+f"(d[6]), "+f"(d[7]), "+f"(d[8]), "+f"(d[9]), "+f"(d[10]), "+f"(d[11])
   : "r"(a[0]), "r"(a[1]), "r"(a[2]), "r"(a[3]), "l"(db), "r"(scale_d));
}
template <> __device__ __forceinline__ void wgmma_rs<32>(float (&d)[64], const uint32_t (&a)[4], uint64_t db, int scale_d) {
  asm volatile("{\n.reg .pred p;\nsetp.ne.b32 p, %21, 0;\n"
   "wgmma.mma_async.sync.aligned.m64n32k16.f32.bf16.bf16 {%0, %1, %2, %3, %4, %5, %6, %7, %8, %9, %10, %11, %12, %13, %14, %15}, {%16,%17,%18,%19}, %20, p, 1, 1, 0;\n}\n"
   : "+f"(d[0]), "+f"(d[1]), "+f"(d[2]), "+f"(d[3]), "+f"(d[4]), "+f"(d[5]), "+f"(d[6]), "+f"(d[7]), "+f"(d[8]), "+f"(d[9]), "+f"(d[10]), "+f"(d[11]), "+f"(d[12]), "+f"(d[13]), "+f"(d[14]), "+f"(d[15])
   : "r"(a[0]), "r"(a[1]), "r"(a[2]), "r"(a[3]), "l"(db), "r"(scale_d));
}
template <> __device__ __forceinline__ void wgmma_rs<40>(float (&d)[64], const uint32_t (&a)[4], uint64_t db, int scale_d) {
  asm volatile("{\n.reg .pred p;\nsetp.ne.b32 p, %25, 0;\n"
   "wgmma.mma_async.sync.aligned.m64n40k16.f32.bf16.bf16 {%0, %1, %2, %3, %4, %5, %6, %7, %8, %9, %10, %11, %12, %13, %14, %15, %16, %17, %18, %19}, {%20,%21,%22,%23}, %24, p, 1, 1, 0;\n}\n"
   : "+f"(d[0]), "+f"(d[1]), "+f"(d[2]), "+f"(d[3]), "+f"(d[4]), "+f"(d[5]), "+f"(d[6]), "+f"(d[7]), "+f"(d[8]), "+f"(d[9]), "+f"(d[10]), "+f"(d[11]), "+f"(d[12]), "+f"(d[13]), "+f"(d[14]), "+f"(d[15]), "+f"(d[16]), "+f"(d[17]), "+f"(d[18]), "+f"(d[19])
   : "r"(a[0]), "r"(a[1]), "r"(a[2]), "r"(a[3]), "l"(db), "r"(scale_d));
}
template <> __device__ __forceinline__ void wgmma_rs<48>(float (&d)[64], const uint32_t (&a)[4], uint64_t db, int scale_d) {
  asm volatile("{\n.reg .pred p;\nsetp.ne.b32 p, %29, 0;\n"
   "wgmma.mma_async.sync.aligned.m64n48k16.f32.bf16.bf16 {%0, %1, %2, %3, %4, %5, %6, %7, %8, %9, %10, %11, %12, %13, %14, %15, %16, %17, %18, %19, %20, %21, %22, %23}, {%24,%25,%26,%27}, %28, p, 1, 1, 0;\n}\n"
   : "+f"(d[0]), "+f"(d[1]), "+f"(d[2]), "+f"(d[3]), "+f"(d[4]), "+f"(d[5]), "+f"(d[6]), "+f"(d[7]), "+f"(d[8]), "+f"(d[9]), "+f"(d[10]), "+f"(d[11]), "+f"(d[12]), "+f"(d[13]), "+f"(d[14]), "+f"(d[15]), "+f"(d[16]), "+f"(d[17]), "+f"(d[18]), "+f"(d[19]), "+f"(d[20]), "+f"(d[21]), "+f"(d[22]), "+f"(d[23])
   : "r"(a[0]), "r"(a[1]), "r"(a[2]), "r"(a[3]), "l"(db), "r"(scale_d));
}
template <> __device__ __forceinline__ void wgmma_rs<56>(float (&d)[64], const uint32_t (&a)[4], uint64_t db, int scale_d) {
  asm volatile("{\n.reg .pred p;\nsetp.ne.b32 p, %33, 0;\n"
   "wgmma.mma_async.sync.aligned.m64n56k16.f32.bf16.bf16 {%0, %1, %2, %3, %4, %5, %6, %7, %8, %9, %10, %11, %12, %13, %14, %15, %16, %17, %18, %19, %20, %21, %22, %23, %24, %25, %26, %27}, {%28,%29,%30,%31}, %32, p, 1, 1, 0;\n}\n"
   : "+f"(d[0]), "+f"(d[1]), "+f"(d[2]), "+f"(d[3]), "+f"(d[4]), "+f"(d[5]), "+f"(d[6]), "+f"(d[7]), "+f"(d[8]), "+f"(d[9]), "+f"(d[10]), "+f"(d[11]), "+f"(d[12]), "+f"(d[13]), "+f"(d[14]), "+f"(d[15]), "+f"(d[16]), "+f"(d[17]), "+f"(d[18]), "+f"(d[19]), "+f"(d[20]), "+f"(d[21]), "+f"(d[22]), "+f"(d[23]), "+f"(d[24]), "+f"(d[25]), "+f"(d[26]), "+f"(d[27])
   : "r"(a[0]), "r"(a[1]), "r"(a[2]), "r"(a[3]), "l"(db), "r"(scale_d));
}
template <> __device__ __forceinline__ void wgmma_rs<64>(float (&d)[64], const uint32_t (&a)[4], uint64_t db, int scale_d) {
  asm volatile("{\n.reg .pred p;\nsetp.ne.b32 p, %37, 0;\n"
   "wgmma.mma_async.sync.aligned.m64n64k16.f32.bf16.bf16 {%0, %1, %2, %3, %4, %5, %6, %7, %8, %9, %10, %11, %12, %13, %14, %15, %16, %17, %18, %19, %20, %21, %22, %23, %24, %25, %26, %27, %28, %29, %30, %31}, {%32,%33,%34,%35}, %36, p, 1, 1, 0;\n}\n"
   : "+f"(d[0]), "+f"(d[1]), "+f"(d[2]), "+f"(d[3]), "+f"(d[4]), "+f"(d[5]), "+f"(d[6]), "+f"(d[7]), "+f"(d[8]), "+f"(d[9]), "+f"(d[10]), "+f"(d[11]), "+f"(d[12]), "+f"(d[13]), "+f"(d[14]), "+f"(d[15]), "+f"(d[16]), "+f"(d[17]), "+f"(d[18]), "+f"(d[19]), "+f"(d[20]), "+f"(d[21]), "+f"(d[22]), "+f"(d[23]), "+f"(d[24]), "+f"(d[25]), "+f"(d[26]), "+f"(d[27]), "+f"(d[28]), "+f"(d[29]), "+f"(d[30]), "+f"(d[31])
   : "r"(a[0]), "r"(a[1]), "r"(a[2]), "r"(a[3]), "l"(db), "r"(scale_d));
}
template <> __device__ __forceinline__ void wgmma_rs<72>(float (&d)[64], const uint32_t (&a)[4], uint64_t db, int scale_d) {
  asm volatile("{\n.reg .pred p;\nsetp.ne.b32 p, %41, 0;\n"
   "wgmma.mma_async.sync.aligned.m64n72k16.f32.bf16.bf16 {%0, %1, %2, %3, %4, %5, %6, %7, %8, %9, %10, %11, %12, %13, %14, %15, %16, %17, %18, %19, %20, %21, %22, %23, %24, %25, %26, %27, %28, %29, %30, %31, %32, %33, %34, %35}, {%36,%37,%38,%39}, %40, p, 1, 1, 0;\n}\n"
   : "+f"(d[0]), "+f"(d[1]), "+f"(d[2]), "+f"(d[3]), "+f"(d[4]), "+f"(d[5]), "+f"(d[6]), "+f"(d[7]), "+f"(d[8]), "+f"(d[9]), "+f"(d[10]), "+f"(d[11]), "+f"(d[12]), "+f"(d[13]), "+f"(d[14]), "+f"(d[15]), "+f"(d[16]), "+f"(d[17]), "+f"(d[18]), "+f"(d[19]), "+f"(d[20]), "+f"(d[21]), "+f"(d[22]), "+f"(d[23]), "+f"(d[24]), "+f"(d[25]), "+f"(d[26]), "+f"(d[27]), "+f"(d[28]), "+f"(d[29]), "+f"(d[30]), "+f"(d[31]), "+f"(d[32]), "+f"(d[33]), "+f"(d[34]), "+f"(d[35])
   : "r"(a[0]), "r"(a[1]), "r"(a[2]), "r"(a[3]), "l"(db), "r"(scale_d));
}
template <> __device__ __forceinline__ void wgmma_rs<80>(float (&d)[64], const uint32_t (&a)[4], uint64_t db, int scale_d) {
  asm volatile("{\n.reg .pred p;\nsetp.ne.b32 p, %45, 0;\n"
   "wgmma.mma_async.sync.aligned.m64n80k16.f32.bf16.bf16 {%0, %1, %2, %3, %4, %5, %6, %7, %8, %9, %10, %11, %12, %13, %14, %15, %16, %17, %18, %19, %20, %21, %22, %23, %24, %25, %26, %27, %28, %29, %30, %31, %32, %33, %34, %35, %36, %37, %38, %39}, {%40,%41,%42,%43}, %44, p, 1, 1, 0;\n}\n"
   : "+f"(d[0]), "+f"(d[1]), "+f"(d[2]), "+f"(d[3]), "+f"(d[4]), "+f"(d[5]), "+f"(d[6]), "+f"(d[7]), "+f"(d[8]), "+f"(d[9]), "+f"(d[10]), "+f"(d[11]), "+f"(d[12]), "+f"(d[13]), "+f"(d[14]), "+f"(d[15]), "+f"(d[16]), "+f"(d[17]), "+f"(d[18]), "+f"(d[19]), "+f"(d[20]), "+f"(d[21]), "+f"(d[22]), "+f"(d[23]), "+f"(d[24]), "+f"(d[25]), "+f"(d[26]), "+f"(d[27]), "+f"(d[28]), "+f"(d[29]), "+f"(d[30]), "+f"(d[31]), "+f"(d[32]), "+f"(d[33]), "+f"(d[34]), "+f"(d[35]), "+f"(d[36]), "+f"(d[37]), "+f"(d[38]), "+f"(d[39])
   : "r"(a[0]), "r"(a[1]), "r"(a[2]), "r"(a[3]), "l"(db), "r"(scale_d));
}
template <> __device__ __forceinline__ void wgmma_rs<88>(float (&d)[64], const uint32_t (&a)[4], uint64_t db, int scale_d) {
  asm volatile("{\n.reg .pred p;\nsetp.ne.b32 p, %49, 0;\n"
   "wgmma.mma_async.sync.aligned.m64n88k16.f32.bf16.bf16 {%0, %1, %2, %3, %4, %5, %6, %7, %8, %9, %10, %11, %12, %13, %14, %15, %16, %17, %18, %19, %20, %21, %22, %23, %24, %25, %26, %27, %28, %29, %30, %31, %32, %33, %34, %35, %36, %37, %38, %39, %40, %41, %42, %43}, {%44,%45,%46,%47}, %48, p, 1, 1, 0;\n}\n"
   : "+f"(d[0]), "+f"(d[1]), "+f"(d[2]), "+f"(d[3]), "+f"(d[4]), "+f"(d[5]), "+f"(d[6]), "+f"(d[7]), "+f"(d[8]), "+f"(d[9]), "+f"(d[10]), "+f"(d[11]), "+f"(d[12]), "+f"(d[13]), "+f"(d[14]), "+f"(d[15]), "+f"(d[16]), "+f"(d[17]), "+f"(d[18]), "+f"(d[19]), "+f"(d[20]), "+f"(d[21]), "+f"(d[22]), "+f"(d[23]), "+f"(d[24]), "+f"(d[25]), "+f"(d[26]), "+f"(d[27]), "+f"(d[28]), "+f"(d[29]), "+f"(d[30]), "+f"(d[31]), "+f"(d[32]), "+f"(d[33]), "+f"(d[34]), "+f"(d[35]), "+f"(d[36]), "+f"(d[37]), "+f"(d[38]), "+f"(d[39]), "+f"(d[40]), "+f"(d[41]), "+f"(d[42]), "+f"(d[43])
   : "r"(a[0]), "r"(a[1]), "r"(a[2]), "r"(a[3]), "l"(db), "r"(scale_d));
}
template <> __device__ __forceinline__ void wgmma_rs<96>(float (&d)[64], const uint32_t (&a)[4], uint64_t db, int scale_d) {
  asm volatile("{\n.reg .pred p;\nsetp.ne.b32 p, %53, 0;\n"
   "wgmma.mma_async.sync.aligned.m64n96k16.f32.bf16.bf16 {%0, %1, %2, %3, %4, %5, %6, %7, %8, %9, %10, %11, %12, %13, %14, %15, %16, %17, %18, %19, %20, %21, %22, %23, %24, %25, %26, %27, %28, %29, %30, %31, %32, %33, %34, %35, %36, %37, %38, %39, %40, %41, %42, %43, %44, %45, %46, %47}, {%48,%49,%50,%51}, %52, p, 1, 1, 0;\n}\n"
   : "+f"(d[0]), "+f"(d[1]), "+f"(d[2]), "+f"(d[3]), "+f"(d[4]), "+f"(d[5]), "+f"(d[6]), "+f"(d[7]), "+f"(d[8]), "+f"(d[9]), "+f"(d[10]), "+f"(d[11]), "+f"(d[12]), "+f"(d[13]), "+f"(d[14]), "+f"(d[15]), "+f"(d[16]), "+f"(d[17]), "+f"(d[18]), "+f"(d[19]), "+f"(d[20]), "+f"(d[21]), "+f"(d[22]), "+f"(d[23]), "+f"(d[24]), "+f"(d[25]), "+f"(d[26]), "+f"(d[27]), "+f"(d[28]), "+f"(d[29]), "+f"(d[30]), "+f"(d[31]), "+f"(d[32]), "+f"(d[33]), "+f"(d[34]), "+f"(d[35]), "+f"(d[36]), "+f"(d[37]), "+f"(d[38]), "+f"(d[39]), "+f"(d[40]), "+f"(d[41]), "+f"(d[42]), "+f"(d[43]), "+f"(d[44]), "+f"(d[45]), "+f"(d[46]), "+f"(d[47])
   : "r"(a[0]), "r"(a[1]), "r"(a[2]), "r"(a[3]), "l"(db), "r"(scale_d));
}
template <> __device__ __forceinline__ void wgmma_rs<104>(float (&d)[64], const uint32_t (&a)[4], uint64_t db, int scale_d) {
  asm volatile("{\n.reg .pred p;\nsetp.ne.b32 p, %57, 0;\n"
   "wgmma.mma_async.sync.aligned.m64n104k16.f32.bf16.bf16 {%0, %1, %2, %3, %4, %5, %6, %7, %8, %9, %10, %11, %12, %13, %14, %15, %16, %17, %18, %19, %20, %21, %22, %23, %24, %25, %26, %27, %28, %29, %30, %31, %32, %33, %34, %35, %36, %37, %38, %39, %40, %41, %42, %43, %44, %45, %46, %47, %48, %49, %50, %51}, {%52,%53,%54,%55}, %56, p, 1, 1, 0;\n}\n"
   : "+f"(d[0]), "+f"(d[1]), "+f"(d[2]), "+f"(d[3]), "+f"(d[4]), "+f"(d[5]), "+f"(d[6]), "+f"(d[7]), "+f"(d[8]), "+f"(d[9]), "+f"(d[10]), "+f"(d[11]), "+f"(d[12]), "+f"(d[13]), "+f"(d[14]), "+f"(d[15]), "+f"(d[16]), "+f"(d[17]), "+f"(d[18]), "+f"(d[19]), "+f"(d[20]), "+f"(d[21]), "+f"(d[22]), "+f"(d[23]), "+f"(d[24]), "+f"(d[25]), "+f"(d[26]), "+f"(d[27]), "+f"(d[28]), "+f"(d[29]), "+f"(d[30]), "+f"(d[31]), "+f"(d[32]), "+f"(d[33]), "+f"(d[34]), "+f"(d[35]), "+f"(d[36]), "+f"(d[37]), "+f"(d[38]), "+f"(d[39]), "+f"(d[40]), "+f"(d[41]), "+f"(d[42]), "+f"(d[43]), "+f"(d[44]), "+f"(d[45]), "+f"(d[46]), "+f"(d[47]), "+f"(d[48]), "+f"(d[49]), "+f"(d[50]), "+f"(d[51])
   : "r"(a[0]), "r"(a[1]), "r"(a[2]), "r"(a[3]), "l"(db), "r"(scale_d));
}
template <> __device__ __forceinline__ void wgmma_rs<112>(float (&d)[64], const uint32_t (&a)[4], uint64_t db, int scale_d) {
  asm volatile("{\n.reg .pred p;\nsetp.ne.b32 p, %61, 0;\n"
   "wgmma.mma_async.sync.aligned.m64n112k16.f32.bf16.bf16 {%0, %1, %2, %3, %4, %5, %6, %7, %8, %9, %10, %11, %12, %13, %14, %15, %16, %17, %18, %19, %20, %21, %22, %23, %24, %25, %26, %27, %28, %29, %30, %31, %32, %33, %34, %35, %36, %37, %38, %39, %40, %41, %42, %43, %44, %45, %46, %47, %48, %49, %50, %51, %52, %53, %54, %55}, {%56,%57,%58,%59}, %60, p, 1, 1, 0;\n}\n"
   : "+f"(d[0]), "+f"(d[1]), "+f"(d[2]), "+f"(d[3]), "+f"(d[4]), "+f"(d[5]), "+f"(d[6]), "+f"(d[7]), "+f"(d[8]), "+f"(d[9]), "+f"(d[10]), "+f"(d[11]), "+f"(d[12]), "+f"(d[13]), "+f"(d[14]), "+f"(d[15]), "+f"(d[16]), "+f"(d[17]), "+f"(d[18]), "+f"(d[19]), "+f"(d[20]), "+f"(d[21]), "+f"(d[22]), "+f"(d[23]), "+f"(d[24]), "+f"(d[25]), "+f"(d[26]), "+f"(d[27]), "+f"(d[28]), "+f"(d[29]), "+f"(d[30]), "+f"(d[31]), "+f"(d[32]), "+f"(d[33]), "+f"(d[34]), "+f"(d[35]), "+f"(d[36]), "+f"(d[37]), "+f"(d[38]), "+f"(d[39]), "+f"(d[40]), "+f"(d[41]), "+f"(d[42]), "+f"(d[43]), "+f"(d[44]), "+f"(d[45]), "+f"(d[46]), "+f"(d[47]), "+f"(d[48]), "+f"(d[49]), "+f"(d[50]), "+f"(d[51]), "+f"(d[52]), "+f"(d[53]), "+f"(d[54]), "+f"(d[55])
   : "r"(a[0]), "r"(a[1]), "r"(a[2]), "r"(a[3]), "l"(db), "r"(scale_d));
}
template <> __device__ __forceinline__ void wgmma_rs<120>(float (&d)[64], const uint32_t (&a)[4], uint64_t db, int scale_d) {
  asm volatile("{\n.reg .pred p;\nsetp.ne.b32 p, %65, 0;\n"
   "wgmma.mma_async.sync.aligned.m64n120k16.f32.bf16.bf16 {%0, %1, %2, %3, %4, %5, %6, %7, %8, %9, %10, %11, %12, %13, %14, %15, %16, %17, %18, %19, %20, %21, %22, %23, %24, %25, %26, %27, %28, %29, %30, %31, %32, %33, %34, %35, %36, %37, %38, %39, %40, %41, %42, %43, %44, %45, %46, %47, %48, %49, %50, %51, %52, %53, %54, %55, %56, %57, %58, %59}, {%60,%61,%62,%63}, %64, p, 1, 1, 0;\n}\n"
   : "+f"(d[0]), "+f"(d[1]), "+f"(d[2]), "+f"(d[3]), "+f"(d[4]), "+f"(d[5]), "+f"(d[6]), "+f"(d[7]), "+f"(d[8]), "+f"(d[9]), "+f"(d[10]), "+f"(d[11]), "+f"(d[12]), "+f"(d[13]), "+f"(d[14]), "+f"(d[15]), "+f"(d[16]), "+f"(d[17]), "+f"(d[18]), "+f"(d[19]), "+f"(d[20]), "+f"(d[21]), "+f"(d[22]), "+f"(d[23]), "+f"(d[24]), "+f"(d[25]), "+f"(d[26]), "+f"(d[27]), "+f"(d[28]), "+f"(d[29]), "+f"(d[30]), "+f"(d[31]), "+f"(d[32]), "+f"(d[33]), "+f"(d[34]), "+f"(d[35]), "+f"(d[36]), "+f"(d[37]), "+f"(d[38]), "+f"(d[39]), "+f"(d[40]), "+f"(d[41]), "+f"(d[42]), "+f"(d[43]), "+f"(d[44]), "+f"(d[45]), "+f"(d[46]), "+f"(d[47]), "+f"(d[48]), "+f"(d[49]), "+f"(d[50]), "+f"(d[51]), "+f"(d[52]), "+f"(d[53]), "+f"(d[54]), "+f"(d[55]), "+f"(d[56]), "+f"(d[57]), "+f"(d[58]), "+f"(d[59])
   : "r"(a[0]), "r"(a[1]), "r"(a[2]), "r"(a[3]), "l"(db), "r"(scale_d));
}
template <> __device__ __forceinline__ void wgmma_rs<128>(float (&d)[64], const uint32_t (&a)[4], uint64_t db, int scale_d) {
  asm volatile("{\n.reg .pred p;\nsetp.ne.b32 p, %69, 0;\n"
   "wgmma.mma_async.sync.aligned.m64n128k16.f32.bf16.bf16 {%0, %1, %2, %3, %4, %5, %6, %7, %8, %9, %10, %11, %12, %13, %14, %15, %16, %17, %18, %19, %20, %21, %22, %23, %24, %25, %26, %27, %28, %29, %30, %31, %32, %33, %34, %35, %36, %37, %38, %39, %40, %41, %42, %43, %44, %45, %46, %47, %48, %49, %50, %51, %52, %53, %54, %55, %56, %57, %58, %59, %60, %61, %62, %63}, {%64,%65,%66,%67}, %68, p, 1, 1, 0;\n}\n"
   : "+f"(d[0]), "+f"(d[1]), "+f"(d[2]), "+f"(d[3]), "+f"(d[4]), "+f"(d[5]), "+f"(d[6]), "+f"(d[7]), "+f"(d[8]), "+f"(d[9]), "+f"(d[10]), "+f"(d[11]), "+f"(d[12]), "+f"(d[13]), "+f"(d[14]), "+f"(d[15]), "+f"(d[16]), "+f"(d[17]), "+f"(d[18]), "+f"(d[19]), "+f"(d[20]), "+f"(d[21]), "+f"(d[22]), "+f"(d[23]), "+f"(d[24]), "+f"(d[25]), "+f"(d[26]), "+f"(d[27]), "+f"(d[28]), "+f"(d[29]), "+f"(d[30]), "+f"(d[31]), "+f"(d[32]), "+f"(d[33]), "+f"(d[34]), "+f"(d[35]), "+f"(d[36]), "+f"(d[37]), "+f"(d[38]), "+f"(d[39]), "+f"(d[40]), "+f"(d[41]), "+f"(d[42]), "+f"(d[43]), "+f"(d[44]), "+f"(d[45]), "+f"(d[46]), "+f"(d[47]), "+f"(d[48]), "+f"(d[49]), "+f"(d[50]), "+f"(d[51]), "+f"(d[52]), "+f"(d[53]), "+f"(d[54]), "+f"(d[55]), "+f"(d[56]), "+f"(d[57]), "+f"(d[58]), "+f"(d[59]), "+f"(d[60]), "+f"(d[61]), "+f"(d[62]), "+f"(d[63])
   : "r"(a[0]), "r"(a[1]), "r"(a[2]), "r"(a[3]), "l"(db), "r"(scale_d));
}
__device__ __forceinline__ void wgmma_rs192(float (&d)[96], const uint32_t (&a)[4], uint64_t db) {
  asm volatile("wgmma.mma_async.sync.aligned.m64n192k16.f32.bf16.bf16 {%0, %1, %2, %3, %4, %5, %6, %7, %8, %9, %10, %11, %12, %13, %14, %15, %16, %17, %18, %19, %20, %21, %22, %23, %24, %25, %26, %27, %28, %29, %30, %31, %32, %33, %34, %35, %36, %37, %38, %39, %40, %41, %42, %43, %44, %45, %46, %47, %48, %49, %50, %51, %52, %53, %54, %55, %56, %57, %58, %59, %60, %61, %62, %63, %64, %65, %66, %67, %68, %69, %70, %71, %72, %73, %74, %75, %76, %77, %78, %79, %80, %81, %82, %83, %84, %85, %86, %87, %88, %89, %90, %91, %92, %93, %94, %95}, {%96,%97,%98,%99}, %100, 1, 1, 1, 0;"
   : "+f"(d[0]), "+f"(d[1]), "+f"(d[2]), "+f"(d[3]), "+f"(d[4]), "+f"(d[5]), "+f"(d[6]), "+f"(d[7]), "+f"(d[8]), "+f"(d[9]), "+f"(d[10]), "+f"(d[11]), "+f"(d[12]), "+f"(d[13]), "+f"(d[14]), "+f"(d[15]), "+f"(d[16]), "+f"(d[17]), "+f"(d[18]), "+f"(d[19]), "+f"(d[20]), "+f"(d[21]), "+f"(d[22]), "+f"(d[23]), "+f"(d[24]), "+f"(d[25]), "+f"(d[26]), "+f"(d[27]), "+f"(d[28]), "+f"(d[29]), "+f"(d[30]), "+f"(d[31]), "+f"(d[32]), "+f"(d[33]), "+f"(d[34]), "+f"(d[35]), "+f"(d[36]), "+f"(d[37]), "+f"(d[38]), "+f"(d[39]), "+f"(d[40]), "+f"(d[41]), "+f"(d[42]), "+f"(d[43]), "+f"(d[44]), "+f"(d[45]), "+f"(d[46]), "+f"(d[47]), "+f"(d[48]), "+f"(d[49]), "+f"(d[50]), "+f"(d[51]), "+f"(d[52]), "+f"(d[53]), "+f"(d[54]), "+f"(d[55]), "+f"(d[56]), "+f"(d[57]), "+f"(d[58]), "+f"(d[59]), "+f"(d[60]), "+f"(d[61]), "+f"(d[62]), "+f"(d[63]), "+f"(d[64]), "+f"(d[65]), "+f"(d[66]), "+f"(d[67]), "+f"(d[68]), "+f"(d[69]), "+f"(d[70]), "+f"(d[71]), "+f"(d[72]), "+f"(d[73]), "+f"(d[74]), "+f"(d[75]), "+f"(d[76]), "+f"(d[77]), "+f"(d[78]), "+f"(d[79]), "+f"(d[80]), "+f"(d[81]), "+f"(d[82]), "+f"(d[83]), "+f"(d[84]), "+f"(d[85]), "+f"(d[86]), "+f"(d[87]), "+f"(d[88]), "+f"(d[89]), "+f"(d[90]), "+f"(d[91]), "+f"(d[92]), "+f"(d[93]), "+f"(d[94]), "+f"(d[95])
   : "r"(a[0]), "r"(a[1]), "r"(a[2]), "r"(a[3]), "l"(db));
}

struct Params {
  const bf16 *x, *shift_k, *ssm_k, *ssm_D, *w2;
  unsigned* fl;
  bf16 *uT, *yT;
  const bf16 *b1, *k, *v;
  bf16* out;
  int nch;
  CUtensorMap tmX, tmW1a, tmW1b, tmAct, tmW2, tmYT, tmOut, tmK, tmV, tmU;
};

template <int G> __device__ __forceinline__ void conv_lds(uint32_t (&a)[2][4], uint32_t ha) {
#pragma unroll
  for (int f = 0; f < 2; f++) {
    const uint32_t x = ha + (f ? 15 - G : G) * 256;
    a[f][0] = lds32(x); a[f][1] = lds32(x + 4); a[f][3] = lds32(x + 8);
  }
}
template <int G> __device__ __forceinline__ void conv_lds(uint32_t (&a)[2][4], uint32_t ha, int off) {
#pragma unroll
  for (int f = 0; f < 2; f++) {
    const uint32_t x = ha + (f ? 15 - G : G) * 256;
    asm volatile("{\n.reg .pred p;\nsetp.eq.s32 p, %4, 0;\n@p ld.shared.u32 %0, [%3];\n@p ld.shared.u32 %1, [%3+4];\n@p ld.shared.u32 %2, [%3+8];\n}\n"
                 : "+r"(a[f][0]), "+r"(a[f][1]), "+r"(a[f][3]) : "r"(x), "r"(off));
  }
}
__device__ __forceinline__ void conv_prmt(uint32_t (&a)[2][4]) {
#pragma unroll
  for (int f = 0; f < 2; f++) {
    asm volatile("prmt.b32 %0, %0, %1, 0x5432;" : "+r"(a[f][0]) : "r"(a[f][1]));
    asm volatile("prmt.b32 %0, %1, %2, 0x5432;" : "=r"(a[f][2]) : "r"(a[f][1]), "r"(a[f][3]));
  }
}
template <int G> __device__ __forceinline__ void conv_group(float (&acc)[64], uint32_t (&A)[4][2][4], uint32_t ha, uint32_t db, int i) {
  auto D = [](uint32_t lo) { return (uint64_t)lo | (8ull << 32); };
  wg_fence();
#define CORD 0
  if (G && CORD) wgmma_rs<8 + 8 * G>(acc, A[G & 3][1], D(db + 120 - 8 * G), 1);
  wgmma_rs<128 - 8 * G>(acc, A[G & 3][0], D(db + 8 * G), G ? 1 : i);
  if (!(G && CORD)) wgmma_rs<8 + 8 * G>(acc, A[G & 3][1], D(db + 120 - 8 * G), 1);
  wg_commit();
  wg_wait<2>();
  if (G < 6) conv_lds<(G + 2) & 7>(A[(G + 2) & 3], ha); else conv_lds<(G + 2) & 7>(A[(G + 2) & 3], ha + 32, i);
  conv_prmt(A[(G + 1) & 3]);
}
__device__ __forceinline__ float4 lds128f(uint32_t a) { float4 v; asm volatile("ld.shared.v4.f32 {%0,%1,%2,%3}, [%4];" : "=f"(v.x), "=f"(v.y), "=f"(v.z), "=f"(v.w) : "r"(a) : "memory"); return v; }
template <int W> __device__ __forceinline__ void conv_send(const uint32_t (&pk)[16][2], uint2 (&r)[4][4], uint32_t xb, int t) {
  constexpr int F = (W + 3) & 3;
  const bool lo = t < W;
  const uint32_t x1 = xb - (lo ? 256 : 0), x2 = xb + (lo ? -256 : 256);
#pragma unroll
  for (int q = 0; q < 16; q++) {
    const bool z = (q & 3) == F;
    if (z) r[q >> 2][0] = make_uint2(lo ? pk[(q + 1) & 15][0] : pk[q][0], lo ? pk[(q + 1) & 15][1] : pk[q][1]);
    if ((q & 3) != (W ? F + 1 : F) && (q || !lo))
      asm volatile("st.shared.v2.u32 [%0], {%1,%2};" ::"r"((z ? x2 : x1) + q * 256), "r"(z && !lo ? pk[(q + 1) & 15][0] : pk[q][0]), "r"(z && !lo ? pk[(q + 1) & 15][1] : pk[q][1]) : "memory");
  }
}
__device__ __forceinline__ void conv_channel(uint32_t sl, uint32_t ex, int w, int lane, int bid, int cz) {
  const int g = lane >> 2, t = lane & 3;
  const uint32_t haddr = sl + CH - 32 + (g + 16 * w + 2 * t) * 4;
  const uint32_t db0 = (uint32_t)make_desc(sl, CU1, 128, 0);
  float acc[64];
  {
    uint32_t A[4][2][4];
    CT(0);
    conv_lds<0>(A[0], haddr); conv_lds<1>(A[1], haddr); conv_prmt(A[0]);
#pragma unroll 1
    for (int i = 0; i < CVI; i++) {
      const uint32_t ha = haddr + i * 32, db = db0 + i;
      conv_group<0>(acc, A, ha, db, i); conv_group<1>(acc, A, ha, db, i); conv_group<2>(acc, A, ha, db, i); conv_group<3>(acc, A, ha, db, i);
      conv_group<4>(acc, A, ha, db, i); conv_group<5>(acc, A, ha, db, i); conv_group<6>(acc, A, ha, db, i); conv_group<7>(acc, A, ha, db, i);
    }
    bar_sync(bid);
    wg_wait<0>();
    CT(4);
  }
#define EXF 0
  const uint32_t xb = (w ? ex + w * 4096 - 4096 : sl + CH) + g * 32 + ((t - w) & 3) * 8 - (t < w ? 256 : 0);
#pragma unroll
  for (int q = 0; q < 16; q++)
    if (q || t >= w) asm volatile("st.shared.v2.u32 [%0], {%1,%2};" ::"r"(xb + q * 256), "r"(pack_bf16(acc[4 * q], acc[4 * q + 2])), "r"(pack_bf16(acc[4 * q + 1], acc[4 * q + 3])) : "memory");
  bar_sync(bid);
  CT(5);
  const uint32_t ya = sl + 63 * 32 + g * 4 - t * 64 - w * 256, ra = lane * 8 + w * 256;
  uint2 r[4][4];
#pragma unroll
  for (int m = 0; m < 16; m++) r[m >> 2][m & 3] = lds64((m & 3 ? ex + (m & 3) * 4096 - 4096 : sl + CH) + ra + (m >> 2) * 1024);
#pragma unroll
  for (int m = 0; m < 4; m++) {
    const uint32_t y = ya - (m & 1) * 1024 + (m < 2 ? CU1 : 0);
    const uint2 r0 = r[m][1], r1 = r[m][2], r2 = r[m][3], r3 = r[m][0];
    const uint32_t v0 = hadd2(hadd2(r3.x, r0.x), hadd2(r1.x, r2.x)), v1 = hadd2(hadd2(r3.y, r0.y), hadd2(r1.y, r2.y));
    sts32(y - (t & 2) * 16, t & 2 ? v1 : v0); sts32(y - 32 + (t & 2) * 16, t & 2 ? v0 : v1);
  }
  CT(6);
  fence_proxy_async_smem();
  __syncwarp();
  CT(7);
}

__device__ __forceinline__ void colsum_out(float (&cs)[8], unsigned* dst, int lane) {
  const bool b4 = lane & 16, b3 = lane & 8;
#pragma unroll
  for (int e = 0; e < 4; e++) cs[e] = (b4 ? cs[e + 4] : cs[e]) + __shfl_xor_sync(0xffffffff, b4 ? cs[e] : cs[e + 4], 16);
#pragma unroll
  for (int e = 0; e < 2; e++) cs[e] = (b3 ? cs[e + 2] : cs[e]) + __shfl_xor_sync(0xffffffff, b3 ? cs[e] : cs[e + 2], 8);
  asm volatile("red.relaxed.gpu.global.add.v2.f32 [%0], {%1,%2};" ::"l"(dst + (lane & 7) * 8 + (lane >> 3) * 2), "f"(cs[0]), "f"(cs[1]) : "memory");
}

__global__ void __cluster_dims__(2, 1, 1) __launch_bounds__(512, 1) h3_ffn_kernel(const __grid_constant__ Params P) {
  extern __shared__ __align__(1024) uint8_t smem_raw[];
  const uint32_t sb = smem_u32(smem_raw);
#define NPRE 1
  const int tid = threadIdx.x;
#define TID0V 0
  constexpr int TID0 = TID0V;
#define XSKIP 0
#define DLY 0
#define KVW 6
#define MAPV 5
  const int cr = blockIdx.x & 1;
  int rb, j;
  {
    const int c = (blockIdx.x >> 1) - 4, q = max(c - 32, 0) * 37 >> 8;
    const int g = c < 0 ? 0 : c < 32 ? c & 7 : c - 31 - q * 7, i = c < 0 ? c + 8 : c < 32 ? c >> 3 : 4 + q;
    rb = g * 2 + cr; j = i & 7;
  }
  const bool extra = blockIdx.x >= 128;
  auto act_col = [](int o, int jj) { return o < 4 ? jj * 256 + o * 64 : 2048 - 256 + jj * 192 + o * 64; };
#define NE 1
  auto load_g1 = [&](int n, bool first) {
    const bool t0 = n < 16;
    const uint32_t st = sb + (n & 3) * (t0 ? SLOT0 : SLOT1), bar = sb + B_FULL1 + (n & 3) * 8;
    int kc = (t0 ? (n ^ rb ^ (j * 2)) & 8 | n & 7 : (n + (rb & 14)) & 15) * 64;
    if (first || n >= 4) {
      mbar_expect_tx(bar, t0 ? SLOT0 : SLOT1);
      tma_2d(st, &P.tmX, bar, kc, rb * 128);
    }
    if (!first) tma_3d_mc(st + 16384 + cr * (t0 ? 16384 : 12288), t0 ? &P.tmW1a : &P.tmW1b, bar, kc + cr * 32, t0 ? j * 4 : 32 + j * 3);
    else if (n < NE) { tma_3d(st + 16384, &P.tmW1a, bar, 0, kc, j * 4); tma_3d(st + 32768, &P.tmW1a, bar, 0, kc + 32, j * 4); }
  };

  if (tid < 32 && elect_one()) {
    asm volatile("prefetch.tensormap [%0];" ::"l"(&P.tmX) : "memory");
    asm volatile("prefetch.tensormap [%0];" ::"l"(&P.tmW1a) : "memory");
#pragma unroll
    for (int i = 0; i < 4; i++) mbar_init(sb + B_FULL1 + i * 8, 1);
    fence_init();
    if (!extra) {
#pragma unroll
      for (int n = 0; n < 4; n++) load_g1(n, true);
    }
  }
  __syncwarp();
  const int warp = __shfl_sync(0xffffffff, tid >> 5, 0), wg = warp >> 2;
  const int lane = tid & 31, t128 = tid & 127, w = warp & 3;
  const int cg = 2 - (wg == 3 ? w : wg);
  const int chs = extra ? 3 : 1, nch = extra ? 11 - XSKIP - (cg >> 1) : P.nch, ch0 = extra ? (blockIdx.x - 100) * 32 + cg : (j * 16 + rb) * nch;
  if (warp && elect_one()) {
    const int i = 2 + 2 * warp;
    mbar_init(sb + BAR_OFF + i * 8, i < 19 ? 1 : i < 31 ? 4 : 8);
    mbar_init(sb + BAR_OFF + i * 8 + 8, i < 18 ? 1 : i < 30 ? 4 : 8);
    if (warp == 13) { mbar_init(sb + B_S3, 4); mbar_init(sb + B_TAB1, 1); mbar_init(sb + B_S4, 3); }
    fence_init();
    if (warp < 9) asm volatile("prefetch.tensormap [%0];" ::"l"(&P.tmW1a + warp) : "memory");
  }
  __syncwarp();
  asm volatile("barrier.cluster.arrive.relaxed.aligned;" ::: "memory");
  if (warp == 12) {
    cta_sync();
    if (!extra && elect_one()) {
#pragma unroll
      for (int n = NE; n < 4; n++) load_g1(n, false);
    }
    __syncwarp();
  }

  if (wg < 2 && !extra) {
    const int g = lane >> 2, t = lane & 3;
    float r0, r1, m0 = ldg_bf(P.x + (size_t)(rb * 128 + warp * 16 + g) * D_), m1 = ldg_bf(P.x + (size_t)(rb * 128 + warp * 16 + g + 8) * D_);
    cta_sync();
    asm volatile("setmaxnreg.inc.sync.aligned.u32 176;");
    const uint32_t xt = sb + XT_OFF + warp * 2048 + (lane & 15) * 128;
    const uint32_t mx = (lane >> 4) ^ (lane & 7);
    const uint32_t descA0 = (uint32_t)make_desc(sb + wg * 8192, 16, 1024, 1);
    const uint32_t descB0 = (uint32_t)make_desc(sb + 16384, 4096, 1024, 1);
    uint32_t emp;
    asm("mapa.shared::cluster.u32 %0, %1, %2;" : "=r"(emp) : "r"(sb + B_EMPTY1), "r"((cr ^ w) & 1));
    const int nsig = t128 & 95;
    auto D64 = [](uint32_t lo) { return (uint64_t)lo | 0x4000004000000000ull; };
    const uint64_t dtab = make_desc(sb + TAB_OFF, 0, 144, 0);
    uint32_t hp[48], pk[32];
    auto park = [&](int i, int bufi) {
#pragma unroll
      for (int q = 0; q < 4; q++) stmatrix4(xt + bufi * 16384 + ((mx ^ (2 * q)) << 4), hp[16 * i + 4 * q], hp[16 * i + 4 * q + 1], hp[16 * i + 4 * q + 2], hp[16 * i + 4 * q + 3]);
    };
    auto publish = [&](int c) {
      fence_proxy_async_smem();
      __syncwarp();
      arrive_if(sb + B_ARDY + (c & 1) * 8, lane);
    };
    auto mish_pair = [&](uint32_t v, float r) { return pack_bf16(mish2(r * bf_lo(v)), mish2(r * bf_hi(v))); };
    auto gone = [&](int c) { mbar_wait(sb + B_AFREE + (c & 1) * 8, (c >> 1) & 1); };

    {
      float acc[64], acd[64];
      auto step0 = [&](int kt) {
        const int s = kt & 3;
        wg_fence();
#pragma unroll
        for (int k = 0; k < 4; k++) {
          wgmma_ss128(acc, D64(descA0 + s * (SLOT0 >> 4) + k * 2), D64(descB0 + s * (SLOT0 >> 4) + (k & 1) * 128 + (k >> 1) * 1024), (kt | k) != 0);
          wgmma_ss128(acd, D64(descA0 + s * (SLOT0 >> 4) + k * 2), D64(descB0 + s * (SLOT0 >> 4) + (k & 1) * 128 + (k >> 1) * 1024 + 512), (kt | k) != 0);
        }
        wg_commit();
        wg_wait<1>();
        arrive_cl(emp + ((kt - 1) & 3) * 8, nsig | (kt == 0));
      };
      {
        float sa[4] = {0.f, 0.f, 0.f, 0.f};
        float cs[8] = {0.f, 0.f, 0.f, 0.f, 0.f, 0.f, 0.f, 0.f};
        const uint32_t sx = xt - XT_OFF + ((mx ^ (2 * (j & 3))) << 4);
        const uint32_t cx = sb + 16384 + (rb & 4) * 4096 + (rb & 3) * 1024 + w * 4096 + (wg * 4 + (lane >> 3)) * 128 + (((lane & 7) ^ (wg * 4 + (lane >> 3))) << 4);
#pragma unroll 1
        for (int kv = 0; kv < 8; kv++) {
          const int kt = uni(kv);
          mbar_wait(sb + B_FULL1 + (kt & 3) * 8, kt >> 2);
          if (kt == 0 && tid == TID0) TS(0);
          uint32_t u[4];
          ldmatrix4(sx + (kt & 3) * SLOT0, u[0], u[1], u[2], u[3]);
          const uint4 q = lds128(cx + (kt & 3) * SLOT0);
          step0(kt);
#pragma unroll
          for (int e = 0; e < 4; e++) {
            const float sh = bf_lo(__float_as_uint((e & 1) ? m1 : m0)), a = bf_lo(u[e]) - sh, b = bf_hi(u[e]) - sh;
            sa[2 * (e & 1)] += a + b;
            sa[2 * (e & 1) + 1] = fmaf(a, a, fmaf(b, b, sa[2 * (e & 1) + 1]));
            cs[2 * e] += bf_lo(((const uint32_t*)&q)[e]); cs[2 * e + 1] += bf_hi(((const uint32_t*)&q)[e]);
          }
          asm volatile("" : "+f"(sa[0]), "+f"(cs[0]));
          bar_sync(1 + wg);
        }
        const bool b1 = t & 2, b0 = t & 1;
#pragma unroll
        for (int e = 0; e < 2; e++) sa[e] = (b1 ? sa[e + 2] : sa[e]) + __shfl_xor_sync(0xffffffff, b1 ? sa[e] : sa[e + 2], 2);
        sa[0] = (b0 ? sa[1] : sa[0]) + __shfl_xor_sync(0xffffffff, b0 ? sa[0] : sa[1], 1);
        asm volatile("red.relaxed.gpu.global.add.f32 [%0], %1;" ::"l"(P.fl + RSUM + (rb * 128 + warp * 16 + g) * 2 + (t & 2) * 8 + (t & 1)), "f"(sa[0]) : "memory");
        colsum_out(cs, P.fl + CSUM + j * 448 + w * 64, lane);
        __syncwarp();
        arrive_if(sb + B_S1, lane);
        if (tid == TID0) TS(8);
      }
#pragma unroll 1
      for (int kv = 8; kv < 16; kv++) {
        const int kt = uni(kv);
        mbar_wait(sb + B_FULL1 + (kt & 3) * 8, (kt >> 2) & 1);
        step0(kt);
      }
      if (tid == TID0) TS(22);
      mbar_wait(sb + B_TABS, 0);
      {
        const uint32_t ra = sb + ROW_OFF + (warp * 16 + g) * 8;
        auto fin = [&](float2 a, float& m, float& r) {
          const float mu = a.x * (1.f / D_), var = fmaxf(fmaf(-mu, mu, a.y * (1.f / D_)), 0.f), nm = -(bf_lo(__float_as_uint(m)) + mu);
          float sd;
          asm("sqrt.approx.f32 %0, %1;" : "=f"(sd) : "f"(round_bf(round_bf(var) + 1e-5f)));
          m = __uint_as_float(pack_bf16(nm, t & 1 ? sd : nm)); r = rcpf(round_bf(sd)) * 1.4426950408889634f;
        };
        fin(lds_f2(ra), m0, r0); fin(lds_f2(ra + 64), m1, r1);
        const uint32_t ar[4] = {t < 2 ? __float_as_uint(m0) : 0, t < 2 ? __float_as_uint(m1) : 0, 0, 0};
        wg_fence();
        wgmma_rs<128>(acc, ar, dtab, 1);
        wgmma_rs<128>(acd, ar, dtab + 144, 1);
        wg_commit();
      }
      wg_wait<1>();
      arrive_cl(emp + 24, nsig);
      wg_wait<0>();
      if (tid == TID0) TS(1);
#define RM4 0
#define RM1 0
#pragma unroll
      for (int k = 31; k >= 0; k--) { hp[k] = pack_bf16(acd[2 * k], acd[2 * k + 1]); asm volatile("" : "+r"(hp[k])); }
#pragma unroll
      for (int k = 31; k >= 0; k--) { pk[k] = pack_bf16(acc[2 * k], acc[2 * k + 1]); asm volatile("" : "+r"(pk[k])); }
    }
    {
      float acc[96];
      mbar_wait(sb + B_FULL1, 0);
      wg_fence();
#pragma unroll
      for (int k = 0; k < 4; k++) wgmma_ss192(acc, D64(descA0 + k * 2), D64(descB0 + (k & 1) * 128 + (k >> 1) * 768), k != 0);
      wg_commit();
#define PEEL2 0
      mbar_wait(sb + B_EMPTY1 + 24, 1);
#pragma unroll
      for (int q = 1 + PEEL2; q < 8; q++) stmatrix4(xt + (q >> 2) * 16384 + ((mx ^ (2 * (q & 3))) << 4), pk[4 * q], pk[4 * q + 1], pk[4 * q + 2], pk[4 * q + 3]);
      stmatrix4(xt + (mx << 4), mish_pair(pk[0], r0), mish_pair(pk[1], r1), mish_pair(pk[2], r0), mish_pair(pk[3], r1));
#pragma unroll 1
      for (int kv = 1 + PEEL2; kv < (RM4 ? 8 : 16); kv++) {
        const int kt = uni(kv);
        const int s = kt & 3;
        const uint32_t a0 = xt + (kt & 4) * 4096 + ((mx ^ (2 * s)) << 4);
        uint32_t p[4];
        ldmatrix4(a0, p[0], p[1], p[2], p[3]);
        mbar_wait(sb + B_FULL1 + s * 8, (kt >> 2) & 1);
        wg_fence();
#pragma unroll
        for (int k = 0; k < 4; k++) wgmma_ss192(acc, D64(descA0 + s * (SLOT1 >> 4) + k * 2), D64(descB0 + s * (SLOT1 >> 4) + (k & 1) * 128 + (k >> 1) * 768), 1);
        wg_commit();
        wg_wait<1>();
        arrive_cl(emp + ((kt - 1) & 3) * 8, nsig);
        if (s == 0) publish((kt >> 2) - 1);
        asm volatile("" : "+r"(p[0]), "+r"(p[1]), "+r"(p[2]), "+r"(p[3]));
#pragma unroll
        for (int i = 0; i < 4; i++) p[i] = pack_bf16(mish2((i & 1 ? r1 : r0) * bf_lo(p[i])), mish2((i & 1 ? r1 : r0) * bf_hi(p[i])));
        stmatrix4(a0, p[0], p[1], p[2], p[3]);
        if (!RM4 && s == 2 && kt > 2) {
          gone((kt >> 2) - 1);
          if (kt == 6) park(0, 0);
          if (kt == 10) park(1, 1);
        }
      }
      mbar_wait(sb + B_TAB1, 0);
      {
        const uint32_t ar[4] = {t < 2 ? 0 : __float_as_uint(m0), t < 2 ? 0 : __float_as_uint(m1), 0, 0};
        wg_fence();
        wgmma_rs192(acc, ar, dtab);
        wg_commit();
      }
      publish(3);
      wg_wait<1>();
      arrive_cl(emp + 24, nsig);
      wg_wait<0>();
      if (tid == TID0) TS(2);
#pragma unroll
      for (int k = 47; k >= 0; k--) { hp[k] = pack_bf16(acc[2 * k], acc[2 * k + 1]); asm volatile("" : "+r"(hp[k])); }
    }
    {
      float acc[64];
      auto step2 = [&](int kt, int md = 0) {
        const bool first = md == 1;
        const int rnd = (kt * 205) >> 10, s = kt - rnd * 5;
        mbar_wait(sb + B_FULL2 + s * 8, rnd & 1);
        wg_fence();
#pragma unroll
        for (int k = 0; k < 4; k++) wgmma_ss128(acc, D64(descA0 + s * (SLOT2 >> 4) + k * 2), D64(descB0 + s * (SLOT2 >> 4) + (k & 1) * 128 + (k >> 1) * 512), first && !k ? kt : 1);
        wg_commit();
        wg_wait<1>();
        arrive_cl(emp + 32 + (s == 0 ? 4 : s - 1) * 8, md == 2 ? nsig : nsig | (first ? kt == 0 : kt > 51));
        if (tid == TID0 && (kt & 7) == 7 && kt < 48) TS(23 + (kt >> 3));
      };
#define RM2 1
#define GU 8
#pragma unroll 1
      for (int c = 0; c < 24; c += GU) {
#pragma unroll
        for (int u = 0; u < GU; u++) {
          step2(uni(c + u), u ? 2 : 1);
          if (u == 0 && (c == 8 || c == 16)) publish(3 + (c >> 3));
          asm volatile("" : "+r"(hp[2 * u]), "+r"(hp[2 * u + 1]));
          hp[2 * u] = mish_pair(hp[2 * u], r0); hp[2 * u + 1] = mish_pair(hp[2 * u + 1], r1);
          if (u == 1) gone(2 + (c >> 3));
          if (u & 1) {
            stmatrix4(xt + (c & 8) * 2048 + ((mx ^ ((c & 7) + u - 1)) << 4), hp[2 * u - 2], hp[2 * u - 1], hp[2 * u], hp[2 * u + 1]);
#pragma unroll
            for (int i = 2 * u - 2; i < 48 - 2 * GU; i += (i & 3) == 3 ? 2 * GU - 3 : 1) hp[i] = hp[i + 2 * GU];
          } else asm volatile("" : "+r"(hp[2 * u]), "+r"(hp[2 * u + 1]));
        }
      }
#define SK0 54
#define SK1 52
#define XS 48
#define XN 4
      uint32_t xf[32], sf[32];
#pragma unroll 1
      for (int h = 0; h < 2; h++) {
#pragma unroll 1
        for (int kv = h ? XS + XN : 24; kv < (h ? 56 : XS); kv++) {
          step2(uni(kv));
          if (kv == 24) publish(6);
          if (kv == (wg ? SK1 : SK0)) { if (wg) asm volatile("bar.sync 4, 256;" ::: "memory"); else asm volatile("bar.arrive 4, 256;" ::: "memory"); }
        }
        if (h) break;
        mbar_wait(sb + B_FINX, 0);
        uint32_t mm[2], rh[2], rl[2];
#pragma unroll
        for (int i = 0; i < 2; i++) {
          const float r = (i ? r1 : r0) * 0.6931471805599453f;
          mm[i] = __byte_perm(__float_as_uint(i ? m1 : m0), 0, 0x1010); rh[i] = pack_bf16(r, r);
          const float e = r - bf_lo(rh[i]);
          rl[i] = pack_bf16(e, e);
        }
#pragma unroll
        for (int u = 0; u < XN; u++) {
#pragma unroll
          for (int v = 0; v < 8 / XN; v++) { const int q = u * (8 / XN) + v; ldmatrix4(xt + (q >> 2) * 16384 + ((mx ^ (2 * (q & 3))) << 4), xf[4 * q], xf[4 * q + 1], xf[4 * q + 2], xf[4 * q + 3]); }
          step2(uni(XS + u + h));
#pragma unroll
          for (int v = 0; v < 32 / XN; v++) {
            const int i = u * (32 / XN) + v;
            const uint32_t d = hadd2(xf[i], mm[i & 1]);
            sf[i] = hfma2(d, rh[i & 1], hmul2(d, rl[i & 1]));
            asm volatile("" : "+r"(sf[i]));
          }
        }
      }
      auto ypart = [&]() {
        mbar_wait(sb + B_FINY, 1);
        const uint32_t ya = sb + X0 + wg * 16384 + ((lane & 7) + (lane >> 4) * 8) * 128 + (((2 * w + ((lane >> 3) & 1)) ^ (lane & 7)) << 4);
#pragma unroll
        for (int q = 0; q < 8; q++) {
          uint32_t y[4];
          ldmatrix4t(ya + q * 2048, y[0], y[1], y[2], y[3]);
#pragma unroll
          for (int i = 0; i < 4; i++) { sf[4 * q + i] = hmul2(sf[4 * q + i], y[i]); asm volatile("" : "+r"(sf[4 * q + i])); }
        }
      };
      if (tid == TID0) TS(3);
      ypart();
      wg_wait<0>();
      if (tid == TID0) TS(5);
#pragma unroll
      for (int q = 0; q < 8; q++) {
        uint32_t o[4];
#pragma unroll
        for (int i = 0; i < 4; i++) {
          const float z0 = 0.5f * acc[8 * q + 2 * i], z1 = 0.5f * acc[8 * q + 2 * i + 1];
          o[i] = hfma2(sf[4 * q + i], pack_bf16(fmaf(z0, tanhf_(z0), z0), fmaf(z1, tanhf_(z1), z1)), xf[4 * q + i]);
        }
        stmatrix4(xt + (q >> 2) * 16384 + ((mx ^ (2 * (q & 3))) << 4), o[0], o[1], o[2], o[3]);
        if ((q & 3) == 3) {
          fence_proxy_async_smem();
          __syncwarp();
          if (elect_one()) { tma_store_2d(&P.tmOut, sb + XT_OFF + warp * 2048 + (q >> 2) * 16384, j * 128 + (q >> 2) * 64, rb * 128 + warp * 16); bulk_commit(); }
        }
      }
      if (tid == TID0) TS(6);
      if (elect_one()) bulk_wait_read0();
      if (tid == TID0) TS(7);
    }
  } else if (wg < 3) {
    {
      const uint4* sp = (const uint4*)(P.shift_k + (j * 128 + lane * 4) * 4);
      const uint4 wab[2] = {__ldg(sp), __ldg(sp + 1)};
      cta_sync();
      const uint32_t va = sb + X0 + w * 4096 + lane * 8;
      const uint32_t ua = sb + X0 + lane * 64 + (((3 - w) ^ ((lane >> 1) & 3)) << 4);
#pragma unroll 1
      for (int ps = extra * 2; ps < 2; ps++) {
        uint2 kk[19];
        mbar_wait(sb + B_CFULL, ps);
#pragma unroll
        for (int r = 0; r < 19; r++) kk[r] = lds64(va + 16384 + r * 256);
        uint32_t uu[2][16];
#pragma unroll
        for (int h = 0; h < 2; h++) {
          const uint4 a = wab[h];
          const uint32_t w0 = __byte_perm(a.x, a.z, 0x5410), w1 = __byte_perm(a.x, a.z, 0x7632), w2 = __byte_perm(a.y, a.w, 0x5410), w3 = __byte_perm(a.y, a.w, 0x7632);
#define KK(r_) (h ? kk[r_].y : kk[r_].x)
#pragma unroll
          for (int r = 15; r >= 0; r--) {
            uu[h][r] = hfma2(KK(r + 3), w0, hfma2(KK(r + 2), w1, hfma2(KK(r + 1), w2, hmul2(KK(r), w3))));
            asm volatile("" : "+r"(uu[h][r]));
            if (h == 0 && r == 15) { __syncwarp(); arrive_if(sb + B_YRDY, lane); arrive_if(sb + B_S2, lane | (ps ^ 1)); }
          }
#undef KK
        }
        mbar_wait(sb + B_CFULL + 8, ps);
#pragma unroll
        for (int r = 0; r < 16; r++) {
          const uint2 v = lds64(va + r * 256);
          uu[0][r] = hmul2(uu[0][r], v.x); uu[1][r] = hmul2(uu[1][r], v.y);
          asm volatile("" : "+r"(uu[0][r]), "+r"(uu[1][r]));
        }
        bar_sync(3);
#pragma unroll
        for (int h = 0; h < 2; h++) {
#pragma unroll
          for (int p = 0; p < 2; p++) {
#define UW(t_, sel) __byte_perm(uu[h][15 - 4 * (t_) - 2 * p], uu[h][14 - 4 * (t_) - 2 * p], sel)
            sts128(ua + h * 8192 + p * 2048, UW(0, 0x5410), UW(1, 0x5410), UW(2, 0x5410), UW(3, 0x5410));
            sts128(ua + h * 8192 + p * 2048 + 4096, UW(0, 0x7632), UW(1, 0x7632), UW(2, 0x7632), UW(3, 0x7632));
#undef UW
          }
        }
        fence_proxy_async_smem();
        __syncwarp();
        arrive_if(sb + B_YRDY + 8, lane);
        if (t128 + 1 == 1) TS(30 + ps);
      }
    }
    if (!extra) {
      mbar_wait(sb + B_FINY, 0);
      const uint32_t a0 = sb + 16384 + cr * 12288 + w * 4096 + (lane >> 3) * 128 + (((lane & 7) ^ (lane >> 3)) << 4);
      if (w < 3) {
        float cs[8] = {0.f, 0.f, 0.f, 0.f, 0.f, 0.f, 0.f, 0.f};
#define CSN 2
#pragma unroll 1
        for (int n = 0; n < 16; n += CSN) {
          uint4 q[CSN];
#pragma unroll
          for (int i = 0; i < CSN; i++) q[i] = lds128((a0 ^ (i & 1) * 64) + (n >> 3) * SLOT1 + ((n & 7) + i) * 512);
#pragma unroll
          for (int i = 4 * CSN - 1; i >= 0; i--) {
            const uint32_t u = ((const uint32_t*)q)[i];
            cs[2 * (i & 3)] += bf_lo(u); cs[2 * (i & 3) + 1] += bf_hi(u);
          }
        }
        arrive_if(sb + B_S4, lane);
        colsum_out(cs, P.fl + CSUM + j * 448 + 256 + w * 64, lane);
        __syncwarp();
      }
      arrive_if(sb + B_S3, lane);
    }
    {
#pragma unroll 1
      for (int c = 0; c < nch; c++) {
        const int s = c & 1;
        mbar_wait(sb + B_CRDY - cg * 32 + s * 8, (c >> 1) & 1);
        conv_channel(sb + X0 - cg * 32768 + s * CSLOT, sb + EX_OFF - cg * 32768, w, lane, 1 + wg, (c - CSEL) | t128 | cg);
        arrive_if(sb + B_YRDY - cg * 16 + s * 8, lane);
        if (t128 + cg == 0 && c < 8) TS(12 + c);
      }
    }
  } else {
    asm volatile("setmaxnreg.dec.sync.aligned.u32 32;");
    if (w) cta_sync();
    if (w == 0 && !extra) {
      if (elect_one()) {
#define W2V 4
#define PD 8
        auto pf_w2 = [&](int n) { if (W2V == 4 && (unsigned)n < 56) prefetch_l2(P.w2 + act_col(n >> 3, n & 7) * D_ + blockIdx.x * 512, 1024); };
#pragma unroll 1
        for (int n = 4; n < 32; n++) {
          mbar_wait(sb + B_EMPTY1 + (n & 3) * 8, ((n >> 2) - 1) & 1);
          if (n == 20) mbar_wait(sb + B_S4, 0);
          load_g1(n, false);
#define PFB 10
          if ((unsigned)(n - PFB) < 2) asm volatile("cp.async.bulk.prefetch.tensor.3d.L2.global [%0, {%1, %2, %3}];" ::"l"(&P.tmW1b), "r"(0), "r"(((n - PFB + (rb & 14)) & 15) * 64 + cr * 32), "r"(32 + j * 3) : "memory");
          pf_w2(n - 32 + PD);
        }
        int s = 0; uint32_t ph = 1, seen = 0;
#pragma unroll 1
        for (int n = 0; n < 56; n++) {
          if (!(n & 7)) {
            const unsigned* f = P.fl + FL_ACT + rb * 32 + (n >> 3);
            if (seen < 8) flag_wait(f, 8);
            seen = flag_ld(f + 1);
          }
          mbar_wait(n < 4 ? sb + B_EMPTY1 + n * 8 : sb + B_EMPTY2 + s * 8, ph);
          const uint32_t st = sb + s * SLOT2, bar = sb + B_FULL2 + s * 8;
          const int kc = act_col(n >> 3, n & 7);
          mbar_expect_tx(bar, 32768);
          tma_2d(st, &P.tmAct, bar, kc, rb * 128);
          tma_3d_mc(st + 16384 + cr * 8192, &P.tmW2, bar, kc + cr * 32, j * 2);
          pf_w2(n + PD);
          if (++s == 5) { s = 0; ph ^= 1; }
        }
        mbar_arrive(sb + B_DONE);
      }
    } else if (w == 1 && !extra) {
      if (elect_one()) {
#pragma unroll 1
        for (int n = 0; n < 10; n++) mbar_wait(sb + B_FULL1 + (n & 1) * 8, (n >> 1) & 1);
        mbar_arrive(sb + B_FINY);
#pragma unroll 1
        for (int c = 0; c < 7; c++) {
          mbar_wait(sb + B_ARDY + (c & 1) * 8, (c >> 1) & 1);
          tma_store_2d(&P.tmAct, sb + XT_OFF + (c & 1) * 16384, act_col(c, j), rb * 128);
          bulk_commit();
          bulk_wait_read0();
          mbar_arrive(sb + B_AFREE + (c & 1) * 8);
          bulk_wait0();
          flag_add(P.fl + FL_ACT + rb * 32 + c);
        }
        mbar_expect_tx(sb + B_FINX, 32768);
        tma_2d(sb + XT_OFF, &P.tmX, sb + B_FINX, j * 128, rb * 128);
        tma_2d(sb + XT_OFF + 16384, &P.tmX, sb + B_FINX, j * 128 + 64, rb * 128);
      }
    } else if (w < 3) {
      if (elect_one() && !extra) {
        if (j != nch) {
          mbar_wait(sb + B_FULL1 + (KVW & 3) * 8, 0);
          if (KVW >= 4) mbar_wait(sb + B_FULL1 + (KVW & 3) * 8, 1);
          if (KVW >= 8) mbar_wait(sb + B_FULL1 + (KVW & 3) * 8, 0);
        }
#pragma unroll 1
        for (int ps = 0; ps < 3; ps++) {
          if (ps < 2) {
            mbar_wait(sb + B_YRDY, ps ^ 1);
            mbar_expect_tx(sb + B_CFULL, 67 * 256);
            tma_2d(sb + KB_OFF, &P.tmK, sb + B_CFULL, j * 128, rb * 128 + ps * 64 - 3);
          }
          if (ps > 0) {
            mbar_wait(sb + B_YRDY + 8, ps - 1);
            asm volatile("cp.async.bulk.tensor.4d.global.shared::cta.bulk_group [%0, {%2, %3, %4, %4}], [%1];" ::"l"(&P.tmU), "r"(sb + X0), "r"(1024 - rb * 64 - ps * 32), "r"(j * 32), "r"(0) : "memory");
            bulk_commit();
            bulk_wait_read0();
          }
          if (ps < 2) {
            mbar_expect_tx(sb + B_CFULL + 8, 16384);
            tma_2d(sb + X0, &P.tmV, sb + B_CFULL + 8, j * 128, rb * 128 + ps * 64);
          }
        }
        prefetch_l2(P.ssm_k + (size_t)ch0 * S_, 8192);
      }
      __syncwarp();
      sts128(sb + X0 - cg * 32768 + 2048 + (lane & 7) * 16 + ((lane >> 3) & 1) * CU1 + (lane >> 4) * CSLOT, 0, 0, 0, 0);
      sts128(sb + EX_OFF - cg * 32768 + 15 * 256 + (lane & 15) * 16 + (lane >> 4) * 4096, 0, 0, 0, 0);
      sts128(sb + EX_OFF - cg * 32768 + 15 * 256 + (lane & 15) * 16 + 8192, 0, 0, 0, 0);
      fence_proxy_async_smem();
      __syncwarp();
      if (elect_one()) {
        unsigned* fc = P.fl + (ch0 >> 7) * 32;
        const int n1 = max((ch0 & 127) + nch - 128, 0);
        if (!extra) { bulk_wait0(); flag_add(P.fl + FL_U + j * 32); }
        TS(29);
        flag_wait(fc + FL_U, 16);
        if (n1) flag_wait(fc + FL_U + 32, 16);
        for (const unsigned t0 = clock(); (unsigned)clock() - t0 < (unsigned)(extra ? cg * 1400 : DLY););
        TS(11);
#pragma unroll 1
        for (int c = 0; c < nch + 2; c++) {
          const int s = c & 1, ch = ch0 + c * chs;
          const uint32_t sl = sb + X0 - cg * 32768 + s * CSLOT, bar = sb + B_CFULL - cg * 32 + s * 8, ph = (c >> 1) & 1;
          if (c >= 2) {
            mbar_wait(sb + B_YRDY - cg * 16 + s * 8, ph ^ 1);
            bulk_s2g(P.yT + (size_t)(ch - 2 * chs) * S_, sl, 2048);
            bulk_s2g(P.yT + (size_t)(ch - 2 * chs) * S_ + 1024, sl + CU1, 2048);
            bulk_commit();
            bulk_wait_read0();
          }
          if (c < nch) {
            mbar_expect_tx(bar, 8192);
            bulk_g2s(sl + CH, P.ssm_k + (size_t)ch * S_, 4096, bar);
            bulk_g2s(sl, P.uT + (size_t)ch * S_, 2048, bar);
            bulk_g2s(sl + CU1, P.uT + (size_t)ch * S_ + 1024, 2048, bar);
            const uint32_t dv = __bfloat16_as_ushort(P.ssm_D[ch]);
            mbar_wait(bar, ph);
            asm volatile("{\n.reg .b32 h;\nld.shared.u32 h, [%0];\nadd.rn.bf16x2 h, h, %1;\nst.shared.u16 [%0], h;\n}\n" ::"r"(sl + CH), "r"(dv) : "memory");
            fence_proxy_async_smem();
            mbar_arrive(bar + 16);
          }
        }
        bulk_wait0(); flag_add(fc + FL_Y, nch - n1 + (extra ? XSKIP : 0));
        if (n1) flag_add(fc + FL_Y + 32, n1);
        if (!extra) {
          mbar_wait(sb + B_FINX, 0);
          flag_wait(P.fl + FL_Y + j * 32, 128);
          TS(19);
          mbar_expect_tx(sb + B_FINY, 32768);
          tma_2d(sb + X0, &P.tmYT, sb + B_FINY, rb * 128, j * 128);
          tma_2d(sb + X0 + 16384, &P.tmYT, sb + B_FINY, rb * 128 + 64, j * 128);
          mbar_wait(sb + B_DONE, 0);
        }
        TS(20);
      }
      __syncwarp();
      unsigned old = 0;
      if (lane == 0 && !extra) asm volatile("atom.relaxed.gpu.global.add.u32 %0, [%1], 1;" : "=r"(old) : "l"(P.fl + FL_TICKET) : "memory");
      if (__shfl_sync(0xffffffff, old, 0) == 127) {
#pragma unroll 1
        for (int i = lane; i < FL_WORDS / 4; i += 32) ((uint4*)P.fl)[i] = make_uint4(0, 0, 0, 0);
      }
    } else if (!extra) {
#pragma unroll 1
      for (int ps = 0; ps < 2; ps++) {
        uint2 bb[2];
#pragma unroll
        for (int i = 0; i < 2; i++) bb[i] = ldg64p((const uint2*)(P.b1 + (ps ? 2048 - 256 + j * 192 : j * 256) + min(lane + (2 * ps + i) * 32, 111) * 4));
        if (elect_one()) {
          mbar_wait(sb + (ps ? B_S3 : B_S1), 0);
          fence_gpu(); flag_add(P.fl + FL_CS + ps + j * 32);
          if (!ps) {
            flag_add(P.fl + FL_STATS + rb * 32);
            TS(9);
            flag_wait(P.fl + FL_STATS + rb * 32, 8);
            bulk_g2s(sb + ROW_OFF, P.fl + RSUM + rb * 256, 1024, sb + B_TABS);
          }
          flag_wait(P.fl + FL_CS + ps + j * 32, 16);
        }
        __syncwarp();
        float4 cs[2];
#pragma unroll
        for (int i = 0; i < 2; i++) cs[i] = __ldcg((const float4*)(P.fl + CSUM + j * 448) + min(lane + (2 * ps + i) * 32, 111));
        mbar_wait(sb + B_S2, 0);
#pragma unroll
        for (int i = 0; i < 2; i++) {
          const int tc = min(lane + (2 * ps + i) * 32, 111) - ps * 64;
          const uint32_t ta = sb + TAB_OFF + tc * 64 + (tc >> 1) * 16 + ps * 8;
#pragma unroll
          for (int e = 0; e < 4; e++) {
            const float c = ((const float*)&cs[i])[e], c1 = c - bf_hi(__float_as_uint(c)), c2 = c1 - bf_hi(__float_as_uint(c1));
            const uint32_t lo = __byte_perm(__float_as_uint(c), __float_as_uint(c1), 0x7632),
                           hi = __byte_perm(__float_as_uint(c2), e < 2 ? bb[i].x : bb[i].y, e & 1 ? 0x7632 : 0x5432);
            if (ps) asm volatile("st.shared.v2.u32 [%0], {%1,%2};" ::"r"(ta + e * 16), "r"(lo), "r"(hi) : "memory");
            else sts128(ta + e * 16, lo, hi, 0, 0);
          }
        }
        fence_proxy_async_smem();
        __syncwarp();
        if (elect_one()) { mbar_expect_tx(sb + (ps ? B_TAB1 : B_TABS), ps ? 0 : 1024); TS(ps ? 21 : 10); }
      }
    }
  }
}

typedef CUresult (*EncFn)(CUtensorMap*, CUtensorMapDataType, cuuint32_t, void*, const cuuint64_t*, const cuuint64_t*, const cuuint32_t*,
                          const cuuint32_t*, CUtensorMapInterleave, CUtensorMapSwizzle, CUtensorMapL2promotion, CUtensorMapFloatOOBfill);
static void make_map(EncFn enc, CUtensorMap* m, const void* ptr, int rank, const cuuint64_t* dims, const cuuint64_t* strides, const cuuint32_t* box) {
  cuuint32_t es[4] = {1, 1, 1, 1};
  enc(m, CU_TENSOR_MAP_DATA_TYPE_BFLOAT16, rank, (void*)ptr, dims, strides, box, es, CU_TENSOR_MAP_INTERLEAVE_NONE,
      box[0] == 64 ? CU_TENSOR_MAP_SWIZZLE_128B : box[0] == 32 ? CU_TENSOR_MAP_SWIZZLE_64B : CU_TENSOR_MAP_SWIZZLE_NONE, CU_TENSOR_MAP_L2_PROMOTION_L2_256B, CU_TENSOR_MAP_FLOAT_OOB_FILL_NONE);
}
static void map2d(EncFn enc, CUtensorMap* m, const void* p, uint64_t cols, uint64_t rows, uint32_t bc, uint32_t br) {
  cuuint64_t d[2] = {cols, rows}, s[1] = {cols * 2}; cuuint32_t b[2] = {bc, br};
  make_map(enc, m, p, 2, d, s, b);
}
static void map3d(EncFn enc, CUtensorMap* m, const void* p, uint64_t cols, uint64_t rows, uint32_t nchunk) {
  cuuint64_t d[3] = {64, rows, cols / 64}, s[2] = {cols * 2, 128}; cuuint32_t b[3] = {64, 32, nchunk};
  make_map(enc, m, p, 3, d, s, b);
}

extern "C" void kernel_launch(void* const* d_in, const int* in_sizes, int n_in, void* d_out, int out_size) {
  (void)in_sizes; (void)n_in; (void)out_size;
  void* fp = nullptr; cudaDriverEntryPointQueryResult qr;
  cudaGetDriverEntryPoint("cuTensorMapEncodeTiled", &fp, cudaEnableDefault, &qr);
  EncFn enc = (EncFn)fp;
  void *act, *yT, *uT, *fl;
  cudaGetSymbolAddress(&act, g_act);
  cudaGetSymbolAddress(&yT, g_yT);
  cudaGetSymbolAddress(&uT, g_uT);
  cudaGetSymbolAddress(&fl, g_flags);
  Params P;
  P.out = (bf16*)d_out; P.k = (const bf16*)d_in[1]; P.v = (const bf16*)d_in[2];
  P.yT = (bf16*)yT; P.uT = (bf16*)uT; P.fl = (unsigned*)fl;
  P.x = (const bf16*)d_in[0]; P.shift_k = (const bf16*)d_in[3];
  P.ssm_k = (const bf16*)d_in[4]; P.ssm_D = (const bf16*)d_in[5]; P.b1 = (const bf16*)d_in[8]; P.w2 = (const bf16*)d_in[9];
  map2d(enc, &P.tmX, P.x, D_, S_, 64, 128);
  map3d(enc, &P.tmW1a, d_in[7], F_, D_, 4);
  map3d(enc, &P.tmW1b, d_in[7], F_, D_, 3);
  map2d(enc, &P.tmAct, act, F_, S_, 64, 128);
  map3d(enc, &P.tmW2, P.w2, D_, F_, 2);
  map2d(enc, &P.tmYT, yT, S_, D_, 64, 128);
  map2d(enc, &P.tmOut, d_out, D_, S_, 64, 16);
  map2d(enc, &P.tmK, d_in[1], D_, S_, 128, 67);
  map2d(enc, &P.tmV, d_in[2], D_, S_, 128, 64);
  {
    cuuint64_t d[4] = {1024, D_ / 4, 2, 4}, s[3] = {16384, 2048, 4096}; cuuint32_t b[4] = {32, 32, 2, 4};
    make_map(enc, &P.tmU, uT, 4, d, s, b);
  }
  cudaFuncSetAttribute(h3_ffn_kernel, cudaFuncAttributeMaxDynamicSharedMemorySize, SMEM_BYTES);
  static int ncl = -1;
  if (ncl < 0) {
    cudaLaunchConfig_t cfg = {};
    cfg.gridDim = dim3(132); cfg.blockDim = dim3(512); cfg.dynamicSmemBytes = SMEM_BYTES;
    if (cudaOccupancyMaxActiveClusters(&ncl, h3_ffn_kernel, &cfg) != cudaSuccess) { ncl = 0; cudaGetLastError(); }
  }
  P.nch = ncl >= 66 ? 7 : 8;
  h3_ffn_kernel<<<ncl >= 66 ? 132 : 128, 512, SMEM_BYTES, cudaStreamPerThread>>>(P);
}
```
